```python
import torch

def _softmax(x, axis=-1):
    return torch.softmax(x, dim=axis)
def _gelu(x):
    return torch.nn.functional.gelu(x, approximate="tanh")
def _silu(x):
    return torch.nn.functional.silu(x)
def _sigmoid(x):
    return torch.sigmoid(x)
def _layernorm(x, axis=-1, eps=1e-5):
    m = x.mean(dim=axis, keepdim=True)
    v = x.var(dim=axis, keepdim=True, unbiased=False)
    return (x - m) / torch.sqrt(v + eps)
def _scatter_add(tgt, idx, src, axis=0):
    return tgt.clone().index_add_(axis, idx, src)
def _segment_sum(src, seg, n):
    out = torch.zeros((n,) + src.shape[1:], dtype=src.dtype)
    return out.index_add_(0, seg, src)
def _pad(x, pw):
    flat = tuple(v for pair in reversed(pw) for v in pair)
    return torch.nn.functional.pad(x, flat)

kernel_name = 'concat_heads__spectral_fnet__ssm_conv_h3__prompt'

def setup_inputs():

    _w = (lambda a: (lambda t: t.to(torch.bfloat16) if t.is_floating_point() else t)(torch.as_tensor(a)))
    def _A_setup():
        B, S, D = 1, 2048, 640
        ns = torch.arange(S)[:, None] * torch.arange(S)[None, :]
        nd = torch.arange(D)[:, None] * torch.arange(D)[None, :]
        Ws_re = torch.cos(-2.0 * torch.pi * ns / S).to(float)
        Ws_im = torch.sin(-2.0 * torch.pi * ns / S).to(float)
        Wd_re = torch.cos(-2.0 * torch.pi * nd / D).to(float)
        Wd_im = torch.sin(-2.0 * torch.pi * nd / D).to(float)
        return {
            "x": _w((lambda *s: torch.randn(*s, dtype=torch.bfloat16) * 0.05)(B, S, D)),
            "dft_seq_re": _w(Ws_re),
            "dft_seq_im": _w(Ws_im),
            "dft_hid_re": _w(Wd_re),
            "dft_hid_im": _w(Wd_im),
        }
    _A_in = _A_setup()

    def _B_setup():
        B, S, D = 1, 2048, 640
        ks = 4
        return {
            "q": _w((lambda *s: torch.randn(*s, dtype=torch.bfloat16) * 0.05)(B, S, D)),
            "k": _w((lambda *s: torch.randn(*s, dtype=torch.bfloat16) * 3.2)(B, S, D)),
            "v": _w((lambda *s: torch.randn(*s, dtype=torch.bfloat16) * 3.2)(B, S, D)),
            "shift_k": _w((lambda *s: torch.randn(*s, dtype=torch.bfloat16) * 3.2)(D, ks) * 0.5),
            "ssm_k": _w((lambda *s: torch.randn(*s, dtype=torch.bfloat16) * 3.2)(D, S) * (1.0 / S ** 0.5)),
            "ssm_D": _w((lambda *s: torch.randn(*s, dtype=torch.bfloat16) * 3.2)(D)),
        }
    _B_in = _B_setup()

    return {
        "A_x": _A_in["x"],
        "A_dft_seq_re": _A_in["dft_seq_re"],
        "A_dft_seq_im": _A_in["dft_seq_im"],
        "A_dft_hid_re": _A_in["dft_hid_re"],
        "A_dft_hid_im": _A_in["dft_hid_im"],
        "B_q": _B_in["q"],
        "B_k": _B_in["k"],
        "B_v": _B_in["v"],
        "B_shift_k": _B_in["shift_k"],
        "B_ssm_k": _B_in["ssm_k"],
        "B_ssm_D": _B_in["ssm_D"],
    }

def reference(A_x, A_dft_seq_re, A_dft_seq_im, A_dft_hid_re, A_dft_hid_im, B_q, B_k, B_v, B_shift_k, B_ssm_k, B_ssm_D):
    def _A_ref(x, dft_seq_re, dft_seq_im, dft_hid_re, dft_hid_im):
        a = torch.einsum("bsd,ed->bse", x, dft_hid_re)
        b = torch.einsum("bsd,ed->bse", x, dft_hid_im)
        y = torch.einsum("ts,bse->bte", dft_seq_re, a) - torch.einsum("ts,bse->bte", dft_seq_im, b)
        return y

    def _B_ref(q, k, v, shift_k, ssm_k, ssm_D):
        B, S, D = q.shape
        ks = shift_k.shape[-1]
        k_pad = _pad(k, ((0, 0), (ks - 1, 0), (0, 0)))
        k_shift = torch.zeros_like(k)
        for t in range(ks):
            k_shift = k_shift + k_pad[:, t:t + S, :] * shift_k[:, ks - 1 - t][None, None, :]
        kv = k_shift * v
        L = 2 * S
        kv_pad = _pad(kv, ((0, 0), (0, S), (0, 0)))
        kf_pad = _pad(ssm_k, ((0, 0), (0, S)))
        kv_f = (lambda x, axes=(-2,-1): torch.fft.rfft2(x.float(), dim=axes))(kv_pad[:, None, :, :], axes=(1, 2))
        kf_f = (lambda x, axes=(-2,-1): torch.fft.rfft2(x.float(), dim=axes))(kf_pad[:, None, :], axes=(1, 2))
        kf_f = (lambda x, *d: x.permute(*d))(kf_f, 1, 2, 0)
        y_f = kv_f * kf_f[None, :, :, :]
        y = (lambda x, s, axes=(-2,-1): torch.fft.irfft2(x, s=s, dim=axes).to(torch.bfloat16))(y_f, (1, L), axes=(1, 2))[:, 0, :S, :]
        y = y + kv * ssm_D[None, None, :]
        return q * y

    a = _A_ref(A_x, A_dft_seq_re, A_dft_seq_im, A_dft_hid_re, A_dft_hid_im)
    b = _B_ref(B_q, B_k, B_v, B_shift_k, B_ssm_k, B_ssm_D)
    return torch.concatenate([a, b], axis=-1)
```

```cpp
#include <cuda_runtime.h>
#include <cuda.h>
#include <cuda_bf16.h>
#include <stdint.h>

namespace {

typedef __nv_bfloat16 bf16;
typedef __nv_bfloat162 bf162;

constexpr int NSTG = 5, A_BYTES = 16384, B_BYTES = 20480, STG_BYTES = A_BYTES + B_BYTES;
constexpr int RING = NSTG * STG_BYTES;
constexpr int OFF_SLOTA = 0, OFF_SLOTB = 40960, OFF_W = 81920, OFF_PST = 143360;
constexpr int W_BYTES = 10240, NWS = 6, PHALF = 20480;
constexpr int USLOT = 4608;
constexpr int OFF_U = RING;
constexpr int OFF_K = OFF_U + 5 * USLOT;
constexpr int KE_OFF = 4288, KBUF = 8576;
constexpr int OFF_X = OFF_K + KBUF;
constexpr int OFF_OST = OFF_X + 2048;
constexpr int OFF_BAR = OFF_OST + 3 * 4096;
constexpr int SMEM_BYTES = OFF_BAR + 1024 + 512;
constexpr int OFF_OST2 = 57344;

constexpr int OFF_Q2 = OFF_OST2 + 12 * 4096;
constexpr int OFF_L2 = OFF_Q2 + 8 * 4096;
constexpr int LBUF = 5760, LK_BYTES = 3200;

enum { B_FULL = 0, B_EMPTY = 5, B_WFULL = 10, B_WEMPTY = 16, B_PFULL = 22, B_PFREE = 37, B_STAGED = 40, B_XFREE = 42,
       B_XFULL = 44, B_KFULL = 46, B_KFREE = 50, B_UFULL = 54, B_OFULL = 66, B_OFREE = 78, B_QFULL = 81, B_LFULL = 89, B_COUNT = 101 };

struct Params {
  const bf16 *q, *k, *v, *shift_k, *ssm_k, *ssm_D;
  bf16* out;
  int nA;
};

__device__ __align__(1024) unsigned char g_pscr[16 * 8 * 40960];
__device__ unsigned int g_flag[16 * 8 * 4];
#define PSTAMP(i)
#define PGT(i)
#define PZERO(lo, hi)
#define PDUMP(lo, hi)

__device__ __forceinline__ uint32_t smem_u32(const void* p) { return (uint32_t)__cvta_generic_to_shared(p); }
__device__ __forceinline__ uint64_t make_desc(uint32_t saddr, uint32_t lbo, uint32_t sbo, uint32_t swz) {
  return (uint64_t)((saddr & 0x3FFFF) >> 4) | ((uint64_t)(lbo >> 4) << 16) | ((uint64_t)(sbo >> 4) << 32) | ((uint64_t)swz << 62);
}
__device__ __forceinline__ void mbar_init(uint32_t bar, uint32_t cnt) { asm volatile("mbarrier.init.shared::cta.b64 [%0], %1;" ::"r"(bar), "r"(cnt) : "memory"); }
__device__ __forceinline__ void mbar_expect_tx(uint32_t bar, uint32_t bytes) { asm volatile("mbarrier.arrive.expect_tx.shared::cta.b64 _, [%0], %1;" ::"r"(bar), "r"(bytes) : "memory"); }
__device__ __forceinline__ void mbar_arrive(uint32_t bar) { asm volatile("mbarrier.arrive.shared::cta.b64 _, [%0];" ::"r"(bar) : "memory"); }
__device__ __forceinline__ uint32_t mapa(uint32_t a, uint32_t cta) { uint32_t r; asm("mapa.shared::cluster.u32 %0, %1, %2;" : "=r"(r) : "r"(a), "r"(cta)); return r; }
__device__ __forceinline__ void mbar_arrive_rem(uint32_t rbar) { asm volatile("mbarrier.arrive.shared::cluster.b64 _, [%0];" ::"r"(rbar) : "memory"); }
__device__ __forceinline__ void mbar_wait(uint32_t bar, uint32_t parity) {
  asm volatile("{\n.reg .pred p;\n.reg .u32 c;\nmov.u32 c, 0;\nLW:\nmbarrier.try_wait.parity.shared::cta.b64 p, [%0], %1;\n@p bra LD;\n"
               "add.u32 c, c, 1;\nsetp.lt.u32 p, c, 4194304;\n@p bra LW;\ntrap;\nLD:\n}\n" ::"r"(bar), "r"(parity) : "memory");
}
__device__ __forceinline__ void tma2d(uint32_t dst, const CUtensorMap* m, int c0, int c1, uint32_t bar) {
  asm volatile("cp.async.bulk.tensor.2d.shared::cluster.global.mbarrier::complete_tx::bytes [%0], [%1, {%3,%4}], [%2];" ::"r"(dst), "l"(m), "r"(bar), "r"(c0), "r"(c1) : "memory");
}
__device__ __forceinline__ void tma2d_mc(uint32_t dst, const CUtensorMap* m, int c0, int c1, uint32_t bar, uint16_t mask) {
  asm volatile("cp.async.bulk.tensor.2d.shared::cluster.global.mbarrier::complete_tx::bytes.multicast::cluster [%0], [%1, {%3,%4}], [%2], %5;" ::"r"(dst), "l"(m), "r"(bar), "r"(c0), "r"(c1), "h"(mask) : "memory");
}
__device__ __forceinline__ void tma3d_mc(uint32_t dst, const CUtensorMap* m, int c0, int c1, int c2, uint32_t bar, uint16_t mask) {
  asm volatile("cp.async.bulk.tensor.3d.shared::cluster.global.mbarrier::complete_tx::bytes.multicast::cluster [%0], [%1, {%3,%4,%5}], [%2], %6;" ::"r"(dst), "l"(m), "r"(bar), "r"(c0), "r"(c1), "r"(c2), "h"(mask) : "memory");
}
__device__ __forceinline__ void tma3d(uint32_t dst, const CUtensorMap* m, int c0, int c1, int c2, uint32_t bar) {
  asm volatile("cp.async.bulk.tensor.3d.shared::cluster.global.mbarrier::complete_tx::bytes [%0], [%1, {%3,%4,%5}], [%2];" ::"r"(dst), "l"(m), "r"(bar), "r"(c0), "r"(c1), "r"(c2) : "memory");
}
__device__ __forceinline__ void tma_store2d(const CUtensorMap* m, uint32_t src, int c0, int c1) {
  asm volatile("cp.async.bulk.tensor.2d.global.shared::cta.bulk_group [%0, {%2,%3}], [%1];" ::"l"(m), "r"(src), "r"(c0), "r"(c1) : "memory");
}
__device__ __forceinline__ void bulk_commit() { asm volatile("cp.async.bulk.commit_group;" ::: "memory"); }
__device__ __forceinline__ void bulk_wait_read() { asm volatile("cp.async.bulk.wait_group.read 0;" ::: "memory"); }
__device__ __forceinline__ void bulk_g2s(uint32_t dst, const void* src, uint32_t bytes, uint32_t bar) {
  asm volatile("cp.async.bulk.shared::cluster.global.mbarrier::complete_tx::bytes [%0], [%1], %2, [%3];" ::"r"(dst), "l"(src), "r"(bytes), "r"(bar) : "memory");
}
__device__ __forceinline__ void bulk_s2s(uint32_t rdst, uint32_t src, uint32_t bytes, uint32_t rbar) {
  asm volatile("cp.async.bulk.shared::cluster.shared::cta.mbarrier::complete_tx::bytes [%0], [%1], %2, [%3];" ::"r"(rdst), "r"(src), "r"(bytes), "r"(rbar) : "memory");
}
__device__ __forceinline__ void bulk_s2g(void* dst, uint32_t src, uint32_t bytes) {
  asm volatile("cp.async.bulk.global.shared::cta.bulk_group [%0], [%1], %2;" ::"l"(dst), "r"(src), "r"(bytes) : "memory");
}
__device__ __forceinline__ void st_async4(uint32_t ra, uint32_t a, uint32_t b, uint32_t c, uint32_t d, uint32_t rbar) {
  asm volatile("st.async.weak.shared::cluster.mbarrier::complete_tx::bytes.v4.b32 [%0], {%1,%2,%3,%4}, [%5];" ::"r"(ra), "r"(a), "r"(b), "r"(c), "r"(d), "r"(rbar) : "memory");
}
__device__ __forceinline__ void st_async2(uint32_t ra, uint32_t a, uint32_t b, uint32_t rbar) {
  asm volatile("st.async.weak.shared::cluster.mbarrier::complete_tx::bytes.v2.b32 [%0], {%1,%2}, [%3];" ::"r"(ra), "r"(a), "r"(b), "r"(rbar) : "memory");
}
__device__ __forceinline__ uint32_t lds32(uint32_t a) { uint32_t v; asm volatile("ld.shared.u32 %0, [%1];" : "=r"(v) : "r"(a)); return v; }
__device__ __forceinline__ uint4 lds128(uint32_t a) { uint4 v; asm volatile("ld.shared.v4.u32 {%0,%1,%2,%3}, [%4];" : "=r"(v.x), "=r"(v.y), "=r"(v.z), "=r"(v.w) : "r"(a) : "memory"); return v; }
__device__ __forceinline__ void sts128(uint32_t a, uint32_t x, uint32_t y, uint32_t z, uint32_t w) { asm volatile("st.shared.v4.u32 [%0], {%1,%2,%3,%4};" ::"r"(a), "r"(x), "r"(y), "r"(z), "r"(w) : "memory"); }
__device__ __forceinline__ uint4 ldg128(const void* p) { uint4 v; asm volatile("ld.global.nc.L1::no_allocate.v4.u32 {%0,%1,%2,%3}, [%4];" : "=r"(v.x), "=r"(v.y), "=r"(v.z), "=r"(v.w) : "l"(p)); return v; }
__device__ __forceinline__ uint4 ldg128c(const void* p) { uint4 v; asm volatile("ld.global.nc.v4.u32 {%0,%1,%2,%3}, [%4];" : "=r"(v.x), "=r"(v.y), "=r"(v.z), "=r"(v.w) : "l"(p)); return v; }
__device__ __forceinline__ uint32_t pack_bf16(float lo, float hi) { uint32_t r; asm("cvt.rn.bf16x2.f32 %0, %1, %2;" : "=r"(r) : "f"(hi), "f"(lo)); return r; }
__device__ __forceinline__ uint32_t bmul(uint32_t a, uint32_t b) { uint32_t r; asm("mul.rn.bf16x2 %0, %1, %2;" : "=r"(r) : "r"(a), "r"(b)); return r; }
__device__ __forceinline__ uint32_t badd(uint32_t a, uint32_t b) { uint32_t r; asm("add.rn.bf16x2 %0, %1, %2;" : "=r"(r) : "r"(a), "r"(b)); return r; }
__device__ __forceinline__ uint32_t prmt(uint32_t a, uint32_t b, uint32_t s) { uint32_t r; asm("prmt.b32 %0, %1, %2, %3;" : "=r"(r) : "r"(a), "r"(b), "r"(s)); return r; }
__device__ __forceinline__ void fence_async() { asm volatile("fence.proxy.async.shared::cta;" ::: "memory"); }
__device__ __forceinline__ void wg_fence() { asm volatile("wgmma.fence.sync.aligned;" ::: "memory"); }
__device__ __forceinline__ void wg_commit() { asm volatile("wgmma.commit_group.sync.aligned;" ::: "memory"); }
template <int N> __device__ __forceinline__ void wg_wait() { asm volatile("wgmma.wait_group.sync.aligned %0;" ::"n"(N) : "memory"); }
__device__ __forceinline__ void bar_sync(int id, int n) { asm volatile("bar.sync %0, %1;" ::"r"(id), "r"(n) : "memory"); }
__device__ __forceinline__ void cluster_arrive() { asm volatile("barrier.cluster.arrive.release.aligned;" ::: "memory"); }
__device__ __forceinline__ void cluster_wait() { asm volatile("barrier.cluster.wait.acquire.aligned;" ::: "memory"); }

template<int TB,int O,int NA> __device__ __forceinline__ void ss160(float (&c)[NA], uint64_t da, uint64_t db, int sd){
 asm volatile("{\n.reg .pred p;\nsetp.ne.b32 p, %82, 0;\nwgmma.mma_async.sync.aligned.m64n160k16.f32.bf16.bf16 {%0,%1,%2,%3,%4,%5,%6,%7,%8,%9,%10,%11,%12,%13,%14,%15,%16,%17,%18,%19,%20,%21,%22,%23,%24,%25,%26,%27,%28,%29,%30,%31,%32,%33,%34,%35,%36,%37,%38,%39,%40,%41,%42,%43,%44,%45,%46,%47,%48,%49,%50,%51,%52,%53,%54,%55,%56,%57,%58,%59,%60,%61,%62,%63,%64,%65,%66,%67,%68,%69,%70,%71,%72,%73,%74,%75,%76,%77,%78,%79},%80,%81,p,1,1,0,%83;\n}\n"
  : "+f"(c[O+0]),"+f"(c[O+1]),"+f"(c[O+2]),"+f"(c[O+3]),"+f"(c[O+4]),"+f"(c[O+5]),"+f"(c[O+6]),"+f"(c[O+7]),"+f"(c[O+8]),"+f"(c[O+9]),"+f"(c[O+10]),"+f"(c[O+11]),"+f"(c[O+12]),"+f"(c[O+13]),"+f"(c[O+14]),"+f"(c[O+15]),"+f"(c[O+16]),"+f"(c[O+17]),"+f"(c[O+18]),"+f"(c[O+19]),"+f"(c[O+20]),"+f"(c[O+21]),"+f"(c[O+22]),"+f"(c[O+23]),"+f"(c[O+24]),"+f"(c[O+25]),"+f"(c[O+26]),"+f"(c[O+27]),"+f"(c[O+28]),"+f"(c[O+29]),"+f"(c[O+30]),"+f"(c[O+31]),"+f"(c[O+32]),"+f"(c[O+33]),"+f"(c[O+34]),"+f"(c[O+35]),"+f"(c[O+36]),"+f"(c[O+37]),"+f"(c[O+38]),"+f"(c[O+39]),"+f"(c[O+40]),"+f"(c[O+41]),"+f"(c[O+42]),"+f"(c[O+43]),"+f"(c[O+44]),"+f"(c[O+45]),"+f"(c[O+46]),"+f"(c[O+47]),"+f"(c[O+48]),"+f"(c[O+49]),"+f"(c[O+50]),"+f"(c[O+51]),"+f"(c[O+52]),"+f"(c[O+53]),"+f"(c[O+54]),"+f"(c[O+55]),"+f"(c[O+56]),"+f"(c[O+57]),"+f"(c[O+58]),"+f"(c[O+59]),"+f"(c[O+60]),"+f"(c[O+61]),"+f"(c[O+62]),"+f"(c[O+63]),"+f"(c[O+64]),"+f"(c[O+65]),"+f"(c[O+66]),"+f"(c[O+67]),"+f"(c[O+68]),"+f"(c[O+69]),"+f"(c[O+70]),"+f"(c[O+71]),"+f"(c[O+72]),"+f"(c[O+73]),"+f"(c[O+74]),"+f"(c[O+75]),"+f"(c[O+76]),"+f"(c[O+77]),"+f"(c[O+78]),"+f"(c[O+79])
  : "l"(da),"l"(db),"r"(sd),"n"(TB));
}
template<int TB,int O,int NA> __device__ __forceinline__ void ss80(float (&c)[NA], uint64_t da, uint64_t db, int sd){
 asm volatile("{\n.reg .pred p;\nsetp.ne.b32 p, %42, 0;\nwgmma.mma_async.sync.aligned.m64n80k16.f32.bf16.bf16 {%0,%1,%2,%3,%4,%5,%6,%7,%8,%9,%10,%11,%12,%13,%14,%15,%16,%17,%18,%19,%20,%21,%22,%23,%24,%25,%26,%27,%28,%29,%30,%31,%32,%33,%34,%35,%36,%37,%38,%39},%40,%41,p,1,1,0,%43;\n}\n"
  : "+f"(c[O+0]),"+f"(c[O+1]),"+f"(c[O+2]),"+f"(c[O+3]),"+f"(c[O+4]),"+f"(c[O+5]),"+f"(c[O+6]),"+f"(c[O+7]),"+f"(c[O+8]),"+f"(c[O+9]),"+f"(c[O+10]),"+f"(c[O+11]),"+f"(c[O+12]),"+f"(c[O+13]),"+f"(c[O+14]),"+f"(c[O+15]),"+f"(c[O+16]),"+f"(c[O+17]),"+f"(c[O+18]),"+f"(c[O+19]),"+f"(c[O+20]),"+f"(c[O+21]),"+f"(c[O+22]),"+f"(c[O+23]),"+f"(c[O+24]),"+f"(c[O+25]),"+f"(c[O+26]),"+f"(c[O+27]),"+f"(c[O+28]),"+f"(c[O+29]),"+f"(c[O+30]),"+f"(c[O+31]),"+f"(c[O+32]),"+f"(c[O+33]),"+f"(c[O+34]),"+f"(c[O+35]),"+f"(c[O+36]),"+f"(c[O+37]),"+f"(c[O+38]),"+f"(c[O+39])
  : "l"(da),"l"(db),"r"(sd),"n"(TB));
}
template<int N> struct RS;
template<> struct RS<160>{ static __device__ __forceinline__ void run(float (&c)[80], const uint32_t* a, uint64_t db, int sd){
 asm volatile("{\n.reg .pred p;\nsetp.ne.b32 p, %85, 0;\nwgmma.mma_async.sync.aligned.m64n160k16.f32.bf16.bf16 {%0,%1,%2,%3,%4,%5,%6,%7,%8,%9,%10,%11,%12,%13,%14,%15,%16,%17,%18,%19,%20,%21,%22,%23,%24,%25,%26,%27,%28,%29,%30,%31,%32,%33,%34,%35,%36,%37,%38,%39,%40,%41,%42,%43,%44,%45,%46,%47,%48,%49,%50,%51,%52,%53,%54,%55,%56,%57,%58,%59,%60,%61,%62,%63,%64,%65,%66,%67,%68,%69,%70,%71,%72,%73,%74,%75,%76,%77,%78,%79},{%80,%81,%82,%83},%84,p,1,1,0;\n}\n"
  : "+f"(c[0]),"+f"(c[1]),"+f"(c[2]),"+f"(c[3]),"+f"(c[4]),"+f"(c[5]),"+f"(c[6]),"+f"(c[7]),"+f"(c[8]),"+f"(c[9]),"+f"(c[10]),"+f"(c[11]),"+f"(c[12]),"+f"(c[13]),"+f"(c[14]),"+f"(c[15]),"+f"(c[16]),"+f"(c[17]),"+f"(c[18]),"+f"(c[19]),"+f"(c[20]),"+f"(c[21]),"+f"(c[22]),"+f"(c[23]),"+f"(c[24]),"+f"(c[25]),"+f"(c[26]),"+f"(c[27]),"+f"(c[28]),"+f"(c[29]),"+f"(c[30]),"+f"(c[31]),"+f"(c[32]),"+f"(c[33]),"+f"(c[34]),"+f"(c[35]),"+f"(c[36]),"+f"(c[37]),"+f"(c[38]),"+f"(c[39]),"+f"(c[40]),"+f"(c[41]),"+f"(c[42]),"+f"(c[43]),"+f"(c[44]),"+f"(c[45]),"+f"(c[46]),"+f"(c[47]),"+f"(c[48]),"+f"(c[49]),"+f"(c[50]),"+f"(c[51]),"+f"(c[52]),"+f"(c[53]),"+f"(c[54]),"+f"(c[55]),"+f"(c[56]),"+f"(c[57]),"+f"(c[58]),"+f"(c[59]),"+f"(c[60]),"+f"(c[61]),"+f"(c[62]),"+f"(c[63]),"+f"(c[64]),"+f"(c[65]),"+f"(c[66]),"+f"(c[67]),"+f"(c[68]),"+f"(c[69]),"+f"(c[70]),"+f"(c[71]),"+f"(c[72]),"+f"(c[73]),"+f"(c[74]),"+f"(c[75]),"+f"(c[76]),"+f"(c[77]),"+f"(c[78]),"+f"(c[79])
  : "r"(a[0]),"r"(a[1]),"r"(a[2]),"r"(a[3]),"l"(db),"r"(sd));
}
 static __device__ __forceinline__ void first(float (&c)[80], const uint32_t* a, uint64_t db){
 asm volatile("{\n.reg .pred p;\nsetp.ne.b32 p, 0, 0;\nwgmma.mma_async.sync.aligned.m64n160k16.f32.bf16.bf16 {%0,%1,%2,%3,%4,%5,%6,%7,%8,%9,%10,%11,%12,%13,%14,%15,%16,%17,%18,%19,%20,%21,%22,%23,%24,%25,%26,%27,%28,%29,%30,%31,%32,%33,%34,%35,%36,%37,%38,%39,%40,%41,%42,%43,%44,%45,%46,%47,%48,%49,%50,%51,%52,%53,%54,%55,%56,%57,%58,%59,%60,%61,%62,%63,%64,%65,%66,%67,%68,%69,%70,%71,%72,%73,%74,%75,%76,%77,%78,%79},{%80,%81,%82,%83},%84,p,1,1,0;\n}\n"
  : "=f"(c[0]),"=f"(c[1]),"=f"(c[2]),"=f"(c[3]),"=f"(c[4]),"=f"(c[5]),"=f"(c[6]),"=f"(c[7]),"=f"(c[8]),"=f"(c[9]),"=f"(c[10]),"=f"(c[11]),"=f"(c[12]),"=f"(c[13]),"=f"(c[14]),"=f"(c[15]),"=f"(c[16]),"=f"(c[17]),"=f"(c[18]),"=f"(c[19]),"=f"(c[20]),"=f"(c[21]),"=f"(c[22]),"=f"(c[23]),"=f"(c[24]),"=f"(c[25]),"=f"(c[26]),"=f"(c[27]),"=f"(c[28]),"=f"(c[29]),"=f"(c[30]),"=f"(c[31]),"=f"(c[32]),"=f"(c[33]),"=f"(c[34]),"=f"(c[35]),"=f"(c[36]),"=f"(c[37]),"=f"(c[38]),"=f"(c[39]),"=f"(c[40]),"=f"(c[41]),"=f"(c[42]),"=f"(c[43]),"=f"(c[44]),"=f"(c[45]),"=f"(c[46]),"=f"(c[47]),"=f"(c[48]),"=f"(c[49]),"=f"(c[50]),"=f"(c[51]),"=f"(c[52]),"=f"(c[53]),"=f"(c[54]),"=f"(c[55]),"=f"(c[56]),"=f"(c[57]),"=f"(c[58]),"=f"(c[59]),"=f"(c[60]),"=f"(c[61]),"=f"(c[62]),"=f"(c[63]),"=f"(c[64]),"=f"(c[65]),"=f"(c[66]),"=f"(c[67]),"=f"(c[68]),"=f"(c[69]),"=f"(c[70]),"=f"(c[71]),"=f"(c[72]),"=f"(c[73]),"=f"(c[74]),"=f"(c[75]),"=f"(c[76]),"=f"(c[77]),"=f"(c[78]),"=f"(c[79])
  : "r"(a[0]),"r"(a[1]),"r"(a[2]),"r"(a[3]),"l"(db));
}
};
template<> struct RS<16>{ static __device__ __forceinline__ void run(float (&c)[64], const uint32_t* a, uint64_t db, int sd){
 asm volatile("{\n.reg .pred p;\nsetp.ne.b32 p, %13, 0;\nwgmma.mma_async.sync.aligned.m64n16k16.f32.bf16.bf16 {%0,%1,%2,%3,%4,%5,%6,%7},{%8,%9,%10,%11},%12,p,1,1,0;\n}\n"
  : "+f"(c[0]),"+f"(c[1]),"+f"(c[2]),"+f"(c[3]),"+f"(c[4]),"+f"(c[5]),"+f"(c[6]),"+f"(c[7])
  : "r"(a[0]),"r"(a[1]),"r"(a[2]),"r"(a[3]),"l"(db),"r"(sd));
}
};
template<> struct RS<32>{ static __device__ __forceinline__ void run(float (&c)[64], const uint32_t* a, uint64_t db, int sd){
 asm volatile("{\n.reg .pred p;\nsetp.ne.b32 p, %21, 0;\nwgmma.mma_async.sync.aligned.m64n32k16.f32.bf16.bf16 {%0,%1,%2,%3,%4,%5,%6,%7,%8,%9,%10,%11,%12,%13,%14,%15},{%16,%17,%18,%19},%20,p,1,1,0;\n}\n"
  : "+f"(c[0]),"+f"(c[1]),"+f"(c[2]),"+f"(c[3]),"+f"(c[4]),"+f"(c[5]),"+f"(c[6]),"+f"(c[7]),"+f"(c[8]),"+f"(c[9]),"+f"(c[10]),"+f"(c[11]),"+f"(c[12]),"+f"(c[13]),"+f"(c[14]),"+f"(c[15])
  : "r"(a[0]),"r"(a[1]),"r"(a[2]),"r"(a[3]),"l"(db),"r"(sd));
}
};
template<> struct RS<48>{ static __device__ __forceinline__ void run(float (&c)[64], const uint32_t* a, uint64_t db, int sd){
 asm volatile("{\n.reg .pred p;\nsetp.ne.b32 p, %29, 0;\nwgmma.mma_async.sync.aligned.m64n48k16.f32.bf16.bf16 {%0,%1,%2,%3,%4,%5,%6,%7,%8,%9,%10,%11,%12,%13,%14,%15,%16,%17,%18,%19,%20,%21,%22,%23},{%24,%25,%26,%27},%28,p,1,1,0;\n}\n"
  : "+f"(c[0]),"+f"(c[1]),"+f"(c[2]),"+f"(c[3]),"+f"(c[4]),"+f"(c[5]),"+f"(c[6]),"+f"(c[7]),"+f"(c[8]),"+f"(c[9]),"+f"(c[10]),"+f"(c[11]),"+f"(c[12]),"+f"(c[13]),"+f"(c[14]),"+f"(c[15]),"+f"(c[16]),"+f"(c[17]),"+f"(c[18]),"+f"(c[19]),"+f"(c[20]),"+f"(c[21]),"+f"(c[22]),"+f"(c[23])
  : "r"(a[0]),"r"(a[1]),"r"(a[2]),"r"(a[3]),"l"(db),"r"(sd));
}
};
template<> struct RS<64>{ static __device__ __forceinline__ void run(float (&c)[64], const uint32_t* a, uint64_t db, int sd){
 asm volatile("{\n.reg .pred p;\nsetp.ne.b32 p, %37, 0;\nwgmma.mma_async.sync.aligned.m64n64k16.f32.bf16.bf16 {%0,%1,%2,%3,%4,%5,%6,%7,%8,%9,%10,%11,%12,%13,%14,%15,%16,%17,%18,%19,%20,%21,%22,%23,%24,%25,%26,%27,%28,%29,%30,%31},{%32,%33,%34,%35},%36,p,1,1,0;\n}\n"
  : "+f"(c[0]),"+f"(c[1]),"+f"(c[2]),"+f"(c[3]),"+f"(c[4]),"+f"(c[5]),"+f"(c[6]),"+f"(c[7]),"+f"(c[8]),"+f"(c[9]),"+f"(c[10]),"+f"(c[11]),"+f"(c[12]),"+f"(c[13]),"+f"(c[14]),"+f"(c[15]),"+f"(c[16]),"+f"(c[17]),"+f"(c[18]),"+f"(c[19]),"+f"(c[20]),"+f"(c[21]),"+f"(c[22]),"+f"(c[23]),"+f"(c[24]),"+f"(c[25]),"+f"(c[26]),"+f"(c[27]),"+f"(c[28]),"+f"(c[29]),"+f"(c[30]),"+f"(c[31])
  : "r"(a[0]),"r"(a[1]),"r"(a[2]),"r"(a[3]),"l"(db),"r"(sd));
}
};
template<> struct RS<80>{ static __device__ __forceinline__ void run(float (&c)[64], const uint32_t* a, uint64_t db, int sd){
 asm volatile("{\n.reg .pred p;\nsetp.ne.b32 p, %45, 0;\nwgmma.mma_async.sync.aligned.m64n80k16.f32.bf16.bf16 {%0,%1,%2,%3,%4,%5,%6,%7,%8,%9,%10,%11,%12,%13,%14,%15,%16,%17,%18,%19,%20,%21,%22,%23,%24,%25,%26,%27,%28,%29,%30,%31,%32,%33,%34,%35,%36,%37,%38,%39},{%40,%41,%42,%43},%44,p,1,1,0;\n}\n"
  : "+f"(c[0]),"+f"(c[1]),"+f"(c[2]),"+f"(c[3]),"+f"(c[4]),"+f"(c[5]),"+f"(c[6]),"+f"(c[7]),"+f"(c[8]),"+f"(c[9]),"+f"(c[10]),"+f"(c[11]),"+f"(c[12]),"+f"(c[13]),"+f"(c[14]),"+f"(c[15]),"+f"(c[16]),"+f"(c[17]),"+f"(c[18]),"+f"(c[19]),"+f"(c[20]),"+f"(c[21]),"+f"(c[22]),"+f"(c[23]),"+f"(c[24]),"+f"(c[25]),"+f"(c[26]),"+f"(c[27]),"+f"(c[28]),"+f"(c[29]),"+f"(c[30]),"+f"(c[31]),"+f"(c[32]),"+f"(c[33]),"+f"(c[34]),"+f"(c[35]),"+f"(c[36]),"+f"(c[37]),"+f"(c[38]),"+f"(c[39])
  : "r"(a[0]),"r"(a[1]),"r"(a[2]),"r"(a[3]),"l"(db),"r"(sd));
}
};
template<> struct RS<96>{ static __device__ __forceinline__ void run(float (&c)[64], const uint32_t* a, uint64_t db, int sd){
 asm volatile("{\n.reg .pred p;\nsetp.ne.b32 p, %53, 0;\nwgmma.mma_async.sync.aligned.m64n96k16.f32.bf16.bf16 {%0,%1,%2,%3,%4,%5,%6,%7,%8,%9,%10,%11,%12,%13,%14,%15,%16,%17,%18,%19,%20,%21,%22,%23,%24,%25,%26,%27,%28,%29,%30,%31,%32,%33,%34,%35,%36,%37,%38,%39,%40,%41,%42,%43,%44,%45,%46,%47},{%48,%49,%50,%51},%52,p,1,1,0;\n}\n"
  : "+f"(c[0]),"+f"(c[1]),"+f"(c[2]),"+f"(c[3]),"+f"(c[4]),"+f"(c[5]),"+f"(c[6]),"+f"(c[7]),"+f"(c[8]),"+f"(c[9]),"+f"(c[10]),"+f"(c[11]),"+f"(c[12]),"+f"(c[13]),"+f"(c[14]),"+f"(c[15]),"+f"(c[16]),"+f"(c[17]),"+f"(c[18]),"+f"(c[19]),"+f"(c[20]),"+f"(c[21]),"+f"(c[22]),"+f"(c[23]),"+f"(c[24]),"+f"(c[25]),"+f"(c[26]),"+f"(c[27]),"+f"(c[28]),"+f"(c[29]),"+f"(c[30]),"+f"(c[31]),"+f"(c[32]),"+f"(c[33]),"+f"(c[34]),"+f"(c[35]),"+f"(c[36]),"+f"(c[37]),"+f"(c[38]),"+f"(c[39]),"+f"(c[40]),"+f"(c[41]),"+f"(c[42]),"+f"(c[43]),"+f"(c[44]),"+f"(c[45]),"+f"(c[46]),"+f"(c[47])
  : "r"(a[0]),"r"(a[1]),"r"(a[2]),"r"(a[3]),"l"(db),"r"(sd));
}
};
template<> struct RS<112>{ static __device__ __forceinline__ void run(float (&c)[64], const uint32_t* a, uint64_t db, int sd){
 asm volatile("{\n.reg .pred p;\nsetp.ne.b32 p, %61, 0;\nwgmma.mma_async.sync.aligned.m64n112k16.f32.bf16.bf16 {%0,%1,%2,%3,%4,%5,%6,%7,%8,%9,%10,%11,%12,%13,%14,%15,%16,%17,%18,%19,%20,%21,%22,%23,%24,%25,%26,%27,%28,%29,%30,%31,%32,%33,%34,%35,%36,%37,%38,%39,%40,%41,%42,%43,%44,%45,%46,%47,%48,%49,%50,%51,%52,%53,%54,%55},{%56,%57,%58,%59},%60,p,1,1,0;\n}\n"
  : "+f"(c[0]),"+f"(c[1]),"+f"(c[2]),"+f"(c[3]),"+f"(c[4]),"+f"(c[5]),"+f"(c[6]),"+f"(c[7]),"+f"(c[8]),"+f"(c[9]),"+f"(c[10]),"+f"(c[11]),"+f"(c[12]),"+f"(c[13]),"+f"(c[14]),"+f"(c[15]),"+f"(c[16]),"+f"(c[17]),"+f"(c[18]),"+f"(c[19]),"+f"(c[20]),"+f"(c[21]),"+f"(c[22]),"+f"(c[23]),"+f"(c[24]),"+f"(c[25]),"+f"(c[26]),"+f"(c[27]),"+f"(c[28]),"+f"(c[29]),"+f"(c[30]),"+f"(c[31]),"+f"(c[32]),"+f"(c[33]),"+f"(c[34]),"+f"(c[35]),"+f"(c[36]),"+f"(c[37]),"+f"(c[38]),"+f"(c[39]),"+f"(c[40]),"+f"(c[41]),"+f"(c[42]),"+f"(c[43]),"+f"(c[44]),"+f"(c[45]),"+f"(c[46]),"+f"(c[47]),"+f"(c[48]),"+f"(c[49]),"+f"(c[50]),"+f"(c[51]),"+f"(c[52]),"+f"(c[53]),"+f"(c[54]),"+f"(c[55])
  : "r"(a[0]),"r"(a[1]),"r"(a[2]),"r"(a[3]),"l"(db),"r"(sd));
}
};
template<> struct RS<128>{ static __device__ __forceinline__ void run(float (&c)[64], const uint32_t* a, uint64_t db, int sd){
 asm volatile("{\n.reg .pred p;\nsetp.ne.b32 p, %69, 0;\nwgmma.mma_async.sync.aligned.m64n128k16.f32.bf16.bf16 {%0,%1,%2,%3,%4,%5,%6,%7,%8,%9,%10,%11,%12,%13,%14,%15,%16,%17,%18,%19,%20,%21,%22,%23,%24,%25,%26,%27,%28,%29,%30,%31,%32,%33,%34,%35,%36,%37,%38,%39,%40,%41,%42,%43,%44,%45,%46,%47,%48,%49,%50,%51,%52,%53,%54,%55,%56,%57,%58,%59,%60,%61,%62,%63},{%64,%65,%66,%67},%68,p,1,1,0;\n}\n"
  : "+f"(c[0]),"+f"(c[1]),"+f"(c[2]),"+f"(c[3]),"+f"(c[4]),"+f"(c[5]),"+f"(c[6]),"+f"(c[7]),"+f"(c[8]),"+f"(c[9]),"+f"(c[10]),"+f"(c[11]),"+f"(c[12]),"+f"(c[13]),"+f"(c[14]),"+f"(c[15]),"+f"(c[16]),"+f"(c[17]),"+f"(c[18]),"+f"(c[19]),"+f"(c[20]),"+f"(c[21]),"+f"(c[22]),"+f"(c[23]),"+f"(c[24]),"+f"(c[25]),"+f"(c[26]),"+f"(c[27]),"+f"(c[28]),"+f"(c[29]),"+f"(c[30]),"+f"(c[31]),"+f"(c[32]),"+f"(c[33]),"+f"(c[34]),"+f"(c[35]),"+f"(c[36]),"+f"(c[37]),"+f"(c[38]),"+f"(c[39]),"+f"(c[40]),"+f"(c[41]),"+f"(c[42]),"+f"(c[43]),"+f"(c[44]),"+f"(c[45]),"+f"(c[46]),"+f"(c[47]),"+f"(c[48]),"+f"(c[49]),"+f"(c[50]),"+f"(c[51]),"+f"(c[52]),"+f"(c[53]),"+f"(c[54]),"+f"(c[55]),"+f"(c[56]),"+f"(c[57]),"+f"(c[58]),"+f"(c[59]),"+f"(c[60]),"+f"(c[61]),"+f"(c[62]),"+f"(c[63])
  : "r"(a[0]),"r"(a[1]),"r"(a[2]),"r"(a[3]),"l"(db),"r"(sd));
}
 static __device__ __forceinline__ void first(float (&c)[64], const uint32_t* a, uint64_t db){
 asm volatile("{\n.reg .pred p;\nsetp.ne.b32 p, 0, 0;\nwgmma.mma_async.sync.aligned.m64n128k16.f32.bf16.bf16 {%0,%1,%2,%3,%4,%5,%6,%7,%8,%9,%10,%11,%12,%13,%14,%15,%16,%17,%18,%19,%20,%21,%22,%23,%24,%25,%26,%27,%28,%29,%30,%31,%32,%33,%34,%35,%36,%37,%38,%39,%40,%41,%42,%43,%44,%45,%46,%47,%48,%49,%50,%51,%52,%53,%54,%55,%56,%57,%58,%59,%60,%61,%62,%63},{%64,%65,%66,%67},%68,p,1,1,0;\n}\n"
  : "=f"(c[0]),"=f"(c[1]),"=f"(c[2]),"=f"(c[3]),"=f"(c[4]),"=f"(c[5]),"=f"(c[6]),"=f"(c[7]),"=f"(c[8]),"=f"(c[9]),"=f"(c[10]),"=f"(c[11]),"=f"(c[12]),"=f"(c[13]),"=f"(c[14]),"=f"(c[15]),"=f"(c[16]),"=f"(c[17]),"=f"(c[18]),"=f"(c[19]),"=f"(c[20]),"=f"(c[21]),"=f"(c[22]),"=f"(c[23]),"=f"(c[24]),"=f"(c[25]),"=f"(c[26]),"=f"(c[27]),"=f"(c[28]),"=f"(c[29]),"=f"(c[30]),"=f"(c[31]),"=f"(c[32]),"=f"(c[33]),"=f"(c[34]),"=f"(c[35]),"=f"(c[36]),"=f"(c[37]),"=f"(c[38]),"=f"(c[39]),"=f"(c[40]),"=f"(c[41]),"=f"(c[42]),"=f"(c[43]),"=f"(c[44]),"=f"(c[45]),"=f"(c[46]),"=f"(c[47]),"=f"(c[48]),"=f"(c[49]),"=f"(c[50]),"=f"(c[51]),"=f"(c[52]),"=f"(c[53]),"=f"(c[54]),"=f"(c[55]),"=f"(c[56]),"=f"(c[57]),"=f"(c[58]),"=f"(c[59]),"=f"(c[60]),"=f"(c[61]),"=f"(c[62]),"=f"(c[63])
  : "r"(a[0]),"r"(a[1]),"r"(a[2]),"r"(a[3]),"l"(db));
}
};

struct Maps { const CUtensorMap *k, *v, *q, *ob; };
__device__ __forceinline__ void p0_issue(const Maps& m, uint32_t buf, uint32_t bar, int col0, int row0) {
  mbar_expect_tx(bar, LBUF);
  tma3d(buf, m.k, col0, (row0 >> 3) - 1, 0, bar);
  tma3d(buf + LK_BYTES, m.v, col0, row0 >> 3, 0, bar);
}
template <int CL>
__device__ __forceinline__ void p0_warp(const Params& p, const Maps& m, uint32_t sb, uint32_t ubase, uint32_t buf, uint32_t bar0,
                                        int toct, int olo, int nb, int row_first, int row_step, int nrounds, int issue_off, int issue_end, int lane) {
  constexpr int CPC = 8 / CL;
  const int rg = lane / nb, ol = lane - rg * nb;
  const bool act = rg < 4;
  uint32_t w[16];
  {
    const int oct = toct + olo + ol;
#pragma unroll
    for (int c = 0; c < 4; c++) {
      uint4 sk = ldg128c(p.shift_k + oct * 32 + c * 8);
      w[4 * c] = prmt(sk.x, sk.z, 0x5410); w[4 * c + 1] = prmt(sk.x, sk.z, 0x7632);
      w[4 * c + 2] = prmt(sk.y, sk.w, 0x5410); w[4 * c + 3] = prmt(sk.y, sk.w, 0x7632);
    }
  }
  const uint32_t ka = buf + (act ? rg : 0) * 80 + (olo + ol) * 16, va = ka + LK_BYTES;
#pragma unroll 1
  for (int r = 0; r < nrounds; r++) {
    const int row0 = row_first + r * row_step;
    const uint32_t bar = CL == 8 ? bar0 + r * 32 : bar0;
    mbar_wait(bar, CL == 8 ? 0 : (r & 1));
    uint4 kr[11], vr[8];
#pragma unroll
    for (int i = 0; i < 11; i++) kr[i] = lds128(ka + (i < 3 ? (i + 5) * 400 : (i - 3) * 400 + 80));
#pragma unroll
    for (int i = 0; i < 8; i++) vr[i] = lds128(va + i * 320);
    uint32_t x[8][4];
#pragma unroll
    for (int i = 0; i < 8; i++) {
      const uint32_t* k0 = (const uint32_t*)&kr[i];
      const uint32_t* k1 = (const uint32_t*)&kr[i + 1];
      const uint32_t* k2 = (const uint32_t*)&kr[i + 2];
      const uint32_t* k3 = (const uint32_t*)&kr[i + 3];
      const uint32_t* vv = (const uint32_t*)&vr[i];
#pragma unroll
      for (int c = 0; c < 4; c++) {
        uint32_t s = badd(bmul(k0[c], w[4 * c + 3]), bmul(k1[c], w[4 * c + 2]));
        s = badd(s, bmul(k2[c], w[4 * c + 1]));
        s = badd(s, bmul(k3[c], w[4 * c]));
        x[i][c] = bmul(s, vv[c]);
        asm volatile("" : "+r"(x[i][c])::"memory");
      }
    }
    __syncwarp();
    if (lane == 0 && row0 + issue_off < issue_end) p0_issue(m, buf, CL == 8 ? bar + 16 : bar, toct * 8, row0 + issue_off);
    if (act) {
      uint32_t off = (uint32_t)(2040 - row0 - rg * 8) * 2;
      off ^= ((off >> 7) & 1) << 4;
#pragma unroll
      for (int ch = 0; ch < 8; ch++) {
        const int c = ch >> 1;
        const uint32_t sel = (ch & 1) ? 0x7632 : 0x5410;
        uint32_t y0 = prmt(x[7][c], x[6][c], sel), y1 = prmt(x[5][c], x[4][c], sel);
        uint32_t y2 = prmt(x[3][c], x[2][c], sel), y3 = prmt(x[1][c], x[0][c], sel);
        const int slot = ol * CPC + (ch % CPC);
        uint32_t ra = mapa(ubase + slot * USLOT + off, ch / CPC);
        uint32_t rb = mapa(sb + OFF_BAR + (B_UFULL + slot) * 8, ch / CPC);
        st_async4(ra, y0, y1, y2, y3, rb);
      }
    }
    __syncwarp();
  }
}

template <int CL>
__device__ __forceinline__ uint32_t ost_addr(uint32_t sb, int task) {
  if (CL == 8) return sb + OFF_OST + (task & 1) * 4096;
  return sb + OFF_OST2 + task * 4096;
}

template <int CL>
__device__ __forceinline__ void conv_out(const Maps& mp, uint32_t sb, uint32_t qbuf, uint32_t qbar, uint32_t qpar, int oct, int task, int seg,
                                         int next_oct, int next_seg, int lane) {
  const int rho = (lane >> 4) * 8 + ((lane & 15) >> 1);
  const uint32_t roff = (uint32_t)(255 - (64 * (lane & 1) + rho)) * 16;
  const uint32_t buf = ost_addr<CL>(sb, task);
  mbar_wait(sb + OFF_BAR + (B_OFULL + task) * 8, 0);
  uint4 y[8];
#pragma unroll
  for (int ch = 0; ch < 8; ch++) y[ch] = lds128(buf + lane * 16 + ch * 512);
  mbar_wait(qbar, qpar);
  uint4 o[8];
#pragma unroll
  for (int m = 0; m < 8; m++) {
    const int wd = m >> 1;
    const int b = (wd & 1) * 8 + (wd >> 1) * 2 + (m & 1);
    const uint4 qv = lds128(qbuf + roff - b * 256);
    const uint32_t sel = (m & 1) ? 0x7632 : 0x5410;
    uint32_t* oo = (uint32_t*)&o[m];
#pragma unroll
    for (int c = 0; c < 4; c++) {
      const uint32_t* ya = (const uint32_t*)&y[2 * c];
      const uint32_t* yb = (const uint32_t*)&y[2 * c + 1];
      oo[c] = bmul(((const uint32_t*)&qv)[c], prmt(ya[wd], yb[wd], sel));
      asm volatile("" : "+r"(oo[c])::"memory");
    }
  }
  __syncwarp();
#pragma unroll
  for (int m = 0; m < 8; m++) {
    const int wd = m >> 1;
    const int b = (wd & 1) * 8 + (wd >> 1) * 2 + (m & 1);
    sts128(buf + roff - b * 256, o[m].x, o[m].y, o[m].z, o[m].w);
  }
  fence_async();
  __syncwarp();
  if (lane == 0) {
    tma_store2d(mp.ob, buf, 640 + oct * 8, seg * 256);
    bulk_commit();
    if (next_oct >= 0) { mbar_expect_tx(qbar, 4096); tma2d(qbuf, mp.q, next_oct * 8, next_seg * 256, qbar); }
    bulk_wait_read();
  }
  __syncwarp();
  if (CL == 8 && task < 3 && lane < 8) mbar_arrive_rem(mapa(sb + OFF_BAR + (B_OFREE + task) * 8, lane));
}

__device__ __forceinline__ void load_a(uint32_t (&a)[16], uint32_t ka) {
#pragma unroll
  for (int i = 0; i < 4; i++) {
    a[4 * i] = lds32(ka + 128 * i);
    a[4 * i + 1] = lds32(ka + 128 * i - 32);
    a[4 * i + 2] = lds32(ka + 128 * i + 16);
    a[4 * i + 3] = lds32(ka + 128 * i - 16);
  }
}

struct ConvCtx {
  uint32_t sb, xw, xr, lane, q, w1;
  uint32_t ulane;
  uint32_t olane;
  float pT0, pT1;
};

template <int CL, int P>
__device__ __forceinline__ void conv_retire(ConvCtx& x, const float* v, float nx, uint32_t uslot, uint32_t D2, int oloc, int chi) {
  constexpr int SEGS = 8 / CL;
  const int srcl = (x.lane & ~3) | ((x.q + 1) & 3);
  float s0 = x.q == 0 ? v[4] : v[0], s1 = x.q == 0 ? nx : v[4];
  float sh0 = __shfl_sync(0xffffffffu, s0, srcl), sh1 = __shfl_sync(0xffffffffu, s1, srcl);
  float T0 = v[2] + v[1], T1 = v[3] + sh0, T2 = v[6] + v[5], T3 = v[7] + sh1;
  uint32_t u0 = 0, u1 = 0;
  if (x.w1 == 0) {
    float p0 = P == 7 ? 0.f : x.pT0, p1 = P == 7 ? 0.f : x.pT1;
    float o0 = x.q == 0 ? T2 : T0, o1 = x.q == 0 ? T3 : T1, o2 = x.q == 0 ? p0 : T2, o3 = x.q == 0 ? p1 : T3;
    sts128(x.xw + (P & 1) * 1024, __float_as_uint(o0), __float_as_uint(o1), __float_as_uint(o2), __float_as_uint(o3));
    x.pT0 = T0; x.pT1 = T1;
  } else {
    asm volatile("ldmatrix.sync.aligned.m8n8.x2.trans.shared.b16 {%0,%1}, [%2];" : "=r"(u0), "=r"(u1) : "r"(uslot + P * 512 + x.ulane) : "memory");
  }
  bar_sync(1, 128);
  if (x.w1 != 0) {
    uint4 r = lds128(x.xr + (P & 1) * 1024);
    uint32_t y0 = pack_bf16(T0 + __uint_as_float(r.x), T1 + __uint_as_float(r.y));
    uint32_t y1 = pack_bf16(T2 + __uint_as_float(r.z), T3 + __uint_as_float(r.w));
    y0 = badd(y0, bmul(u0, D2));
    y1 = badd(y1, bmul(u1, D2));
    constexpr int owner = (7 - P) / SEGS;
    const int task = oloc * SEGS + (7 - P) % SEGS;
    uint32_t ra = mapa(ost_addr<CL>(x.sb, task) + chi * 512 + x.olane, owner);
    uint32_t rb = mapa(x.sb + OFF_BAR + (B_OFULL + task) * 8, owner);
    st_async2(ra, y0, y1, rb);
  }
}

template <int CL>
__device__ __forceinline__ void k_builder(const Params& p, uint32_t sb, int rank, int oct0, int noct, int lane) {
  constexpr int CPC = 8 / CL;
  const int nch = noct * CPC;
#pragma unroll 1
  for (int ci = 0; ci < nch; ci++) {
    const int ch = (oct0 + ci / CPC) * 8 + rank * CPC + ci % CPC;
    const bf16* src = p.ssm_k + (size_t)ch * 2048 + lane * 8;
    uint4 d[8];
    uint32_t pv[8];
#pragma unroll
    for (int i = 0; i < 8; i++) {
      d[i] = ldg128c(src + i * 256);
      pv[i] = (i > 0 || lane > 0) ? __ldg((const uint32_t*)(src + i * 256 - 2)) : 0u;
    }
    if (ci == 0) cluster_wait();
#pragma unroll
    for (int qt = 0; qt < 4; qt++) {
      if (ci > 0) mbar_wait(sb + OFF_BAR + (B_KFREE + qt) * 8, (ci - 1) & 1);
#pragma unroll
      for (int h = 0; h < 2; h++) {
        const int i = 2 * qt + h;
        const uint32_t o = sb + OFF_K + 128 + i * 512 + lane * 16;
        sts128(o + KE_OFF, d[i].x, d[i].y, d[i].z, d[i].w);
        sts128(o, __funnelshift_l(pv[i], d[i].x, 16), __funnelshift_l(d[i].x, d[i].y, 16), __funnelshift_l(d[i].y, d[i].z, 16),
               __funnelshift_l(d[i].z, d[i].w, 16));
      }
      __syncwarp();
      if (lane == 0) mbar_arrive(sb + OFF_BAR + (B_KFULL + qt) * 8);
    }
  }
}

template <int PH>
__device__ __forceinline__ void conv_issue(float (&c)[64], uint32_t (&a)[16], uint64_t d0) {
  constexpr int N = 128 - 16 * PH;
  if (PH > 0) {
#pragma unroll
    for (int i = 0; i < N / 2; i++) asm volatile("mov.b32 %0, %1;" : "=f"(c[i]) : "f"(c[i]) : "memory");
  }
  wg_fence();
  if constexpr (PH == 0) RS<128>::first(c, &a[0], d0);
#pragma unroll
  for (int i = (PH == 0 ? 1 : 0); i < 4; i++) RS<N>::run(c, &a[4 * i], d0 + (4 * PH + i) * 8, 1);
  wg_commit();
}

template <int CL>
__device__ __forceinline__ void conv_main(const Params& p, uint32_t sb, uint32_t ubase, int rank, int oct0, int noct, int tid) {
  constexpr int CPC = 8 / CL;
  const int nch = noct * CPC;
  const int lane = tid & 31, w = tid >> 5, g = lane >> 2, q = lane & 3, w0 = w & 1, w1 = w >> 1;
  ConvCtx x;
  x.sb = sb; x.lane = lane; x.q = q; x.w1 = w1;
  x.xw = sb + OFF_X + w0 * 512 + ((lane & ~3) | ((q + 3) & 3)) * 16;
  x.xr = sb + OFF_X + w0 * 512 + lane * 16;
  x.ulane = (32 * (lane & 15) + 16 * w0) ^ (((lane >> 2) & 1) << 4);
  x.olane = (w0 * 32 + lane) * 8;
  x.pT0 = x.pT1 = 0.f;
  const int e = 112 + 2 * q - 32 * w1 - 8 * w0 - g;
  const uint32_t ka = (g & 1) ? sb + OFF_K + (e + 1) * 2 : sb + OFF_K + KE_OFF + e * 2;
  const uint32_t kbar = sb + OFF_BAR + B_KFULL * 8;
  float c[64];
  float r[9];
#pragma unroll
  for (int i = 0; i < 9; i++) r[i] = 0.f;
  uint32_t a0[16], a1[16];
  uint32_t pslot = 0, pD2 = 0;
  int poloc = 0, pchi = 0;
  mbar_wait(kbar, 0);
  load_a(a0, ka);
  for (int ci = 0; ci < nch; ci++) {
    const int oloc = ci / CPC, chi = rank * CPC + ci % CPC;
    const int ch = (oct0 + oloc) * 8 + chi;
    const int nci = ci + 1;
    const bool more = nci < nch;
    const uint32_t uslot = ubase + ci * USLOT;
    const uint32_t par = ci & 1;
    uint32_t D2 = *(const unsigned short*)(p.ssm_D + ch);
    D2 |= D2 << 16;
    const uint64_t d0 = make_desc(uslot, 16, 256, 3);
    if (tid == 0) PSTAMP(12 + 2 * ci);
    mbar_wait(sb + OFF_BAR + (B_UFULL + ci) * 8, 0);
    fence_async();
    if (tid == 0) PSTAMP(13 + 2 * ci);
    conv_issue<0>(c, a0, d0);
    load_a(a1, ka + 512);
    if (ci > 0) conv_retire<CL, 0>(x, r, r[8], pslot, pD2, poloc, pchi);
    if (CL == 8 && ci >= 2) mbar_wait(sb + OFF_BAR + (B_OFREE + ci - 2) * 8, 0);
    wg_wait<0>();
    if (tid == 0 && ci == 2) PSTAMP(36 + 1);
    conv_issue<1>(c, a1, d0);
    mbar_wait(kbar + 8, par);
    load_a(a0, ka + 1024);
    conv_retire<CL, 7>(x, &c[56], 0.f, uslot, D2, oloc, chi);
    wg_wait<0>();
    if (tid == 0 && ci == 2) PSTAMP(36 + 2);
    conv_issue<2>(c, a0, d0);
    load_a(a1, ka + 1536);
    conv_retire<CL, 6>(x, &c[48], c[56], uslot, D2, oloc, chi);
    if (more && tid == 0) mbar_arrive(sb + OFF_BAR + (B_KFREE + 0) * 8);
    wg_wait<0>();
    if (tid == 0 && ci == 2) PSTAMP(36 + 3);
    conv_issue<3>(c, a1, d0);
    mbar_wait(kbar + 16, par);
    load_a(a0, ka + 2048);
    conv_retire<CL, 5>(x, &c[40], c[48], uslot, D2, oloc, chi);
    wg_wait<0>();
    if (tid == 0 && ci == 2) PSTAMP(36 + 4);
    conv_issue<4>(c, a0, d0);
    load_a(a1, ka + 2560);
    conv_retire<CL, 4>(x, &c[32], c[40], uslot, D2, oloc, chi);
    if (more && tid == 0) mbar_arrive(sb + OFF_BAR + (B_KFREE + 1) * 8);
    wg_wait<0>();
    if (tid == 0 && ci == 2) PSTAMP(36 + 5);
    conv_issue<5>(c, a1, d0);
    mbar_wait(kbar + 24, par);
    load_a(a0, ka + 3072);
    conv_retire<CL, 3>(x, &c[24], c[32], uslot, D2, oloc, chi);
    wg_wait<0>();
    if (tid == 0 && ci == 2) PSTAMP(36 + 6);
    conv_issue<6>(c, a0, d0);
    load_a(a1, ka + 3584);
    conv_retire<CL, 2>(x, &c[16], c[24], uslot, D2, oloc, chi);
    if (more && tid == 0) mbar_arrive(sb + OFF_BAR + (B_KFREE + 2) * 8);
    wg_wait<0>();
    if (tid == 0 && ci == 2) PSTAMP(36 + 7);
    conv_issue<7>(c, a1, d0);
    if (more) { mbar_wait(kbar, par ^ 1); load_a(a0, ka); }
    conv_retire<CL, 1>(x, &c[8], c[16], uslot, D2, oloc, chi);
    if (more && tid == 0) mbar_arrive(sb + OFF_BAR + (B_KFREE + 3) * 8);
    wg_wait<0>();
#pragma unroll
    for (int i = 0; i < 9; i++) asm volatile("mov.b32 %0, %1;" : "=f"(r[i]) : "f"(c[i]) : "memory");
    pslot = uslot; pD2 = D2; poloc = oloc; pchi = chi;
  }
  conv_retire<CL, 0>(x, r, r[8], pslot, pD2, poloc, pchi);
}

template <int CL>
__device__ __forceinline__ void gemm_consumer(const CUtensorMap* mOa, uint32_t sb, int wg, int tid, int rank, int half, int j, int tt) {
  const int lane = tid & 31, w = tid >> 5;
  const uint32_t bars = sb + OFF_BAR;
  constexpr int NREL = CL == 8 ? 5 : 2;
  uint32_t rel = 0;
  if (tid < NREL) {
    int tgt = CL == 8 ? (tid < 4 ? half * 4 + tid : rank ^ 4) : tid;
    rel = mapa(bars + B_EMPTY * 8, tgt);
  }
  float acc[80];
#pragma unroll
  for (int i = 0; i < 80; i++) acc[i] = 0.f;
  int s = 0, sp = 0;
  uint32_t ph = 0;
#pragma unroll 1
  for (int k = 0; k < 32; k++) {
    mbar_wait(bars + (B_FULL + s) * 8, ph);
    if (tid == 0 && wg == 0 && (k & 3) == 0) PSTAMP(44 + (k >> 2));
    const uint32_t a = sb + s * STG_BYTES + wg * 8192, b = sb + s * STG_BYTES + A_BYTES;
    const uint64_t da = make_desc(a, 16, 1024, 1), db = make_desc(b, 2048, 512, 2);
#pragma unroll
    for (int kk = 0; kk < 4; kk++) {
      wg_fence();
      ss160<1, 0>(acc, da + kk * 2, db + (kk >> 1) * (B_BYTES / 32) + (kk & 1) * 64, 1);
      wg_commit();
      wg_wait<1>();
      if (kk == 0 && k > 0 && k <= 30 && tid < NREL) mbar_arrive_rem(rel + sp * 8);
    }
    sp = s;
    if (++s == NSTG) { s = 0; ph ^= 1; }
  }
  wg_wait<0>();
#pragma unroll
  for (int i = 0; i < 80; i++) asm volatile("" : "+f"(acc[i])::"memory");
  if (tid == 0 && wg == 0) PSTAMP(2);
  if (tid < 2) {
    int tgt = CL == 8 ? half * 4 + ((j + tid + 1) & 3) : rank;
    mbar_arrive_rem(mapa(bars + (B_PFREE + tid) * 8, tgt));
  }
  asm volatile("setmaxnreg.inc.sync.aligned.u32 152;");
  uint32_t pk[40];
#pragma unroll
  for (int i = 0; i < 40; i++) { pk[i] = pack_bf16(acc[2 * i], acc[2 * i + 1]); asm volatile("" : "+r"(pk[i])::"memory"); }
  const uint64_t dw0 = make_desc(sb + OFF_W, 16, 512, 2);
#pragma unroll
  for (int c = 0; c < 2; c++) {
    mbar_wait(bars + (B_WFULL + c) * 8, 0);
    wg_fence();
    if (c == 0) RS<160>::first(acc, &pk[0], dw0);
    else RS<160>::run(acc, &pk[8 * c], dw0 + c * (W_BYTES / 16), 1);
    RS<160>::run(acc, &pk[8 * c + 4], dw0 + c * (W_BYTES / 16) + 2, 1);
    wg_commit();
  }
  mbar_wait(bars + (B_EMPTY + 4) * 8, 1);
  {
    const int row = 16 * w + (lane & 7) + 8 * ((lane >> 3) & 1);
    const uint32_t base = sb + OFF_PST + wg * PHALF + row * 64;
    const uint32_t sw = (row >> 1) & 3, hi = lane >> 4;
#pragma unroll
    for (int t = 0; t < 10; t++) {
      uint32_t ad = base + (t >> 1) * 4096 + ((((t & 1) * 2 + hi) ^ sw) << 4);
      asm volatile("stmatrix.sync.aligned.m8n8.x4.shared.b16 [%0], {%1,%2,%3,%4};" ::"r"(ad), "r"(pk[4 * t]), "r"(pk[4 * t + 1]), "r"(pk[4 * t + 2]), "r"(pk[4 * t + 3]) : "memory");
    }
    fence_async();
    __syncwarp();
    if (lane == 0) mbar_arrive(bars + (B_STAGED + wg) * 8);
  }
#pragma unroll
  for (int c = 2; c < 5; c++) {
    mbar_wait(bars + (B_WFULL + c) * 8, 0);
    wg_fence();
    RS<160>::run(acc, &pk[8 * c], dw0 + c * (W_BYTES / 16), 1);
    RS<160>::run(acc, &pk[8 * c + 4], dw0 + c * (W_BYTES / 16) + 2, 1);
    wg_commit();
    wg_wait<1>();
    if (tid == 0) {
      if (c == 2) mbar_arrive(bars + (B_WEMPTY + 0) * 8);
      mbar_arrive(bars + (B_WEMPTY + c - 1) * 8);
    }
  }
  int ws = 5, wsp = 4;
  uint32_t wph = 0;
#pragma unroll 1
  for (int tau = 1; tau < 4; tau++) {
    if (tid == 0 && wg == 0) PSTAMP(2 + tau);
    const uint64_t dp = make_desc(sb + (tau == 2 ? OFF_SLOTB : OFF_SLOTA) + wg * PHALF, 16, 512, 2);
#pragma unroll 1
    for (int c5 = 0; c5 < 5; c5++) {
      mbar_wait(bars + (B_PFULL + (tau - 1) * 5 + c5) * 8, 0);
      mbar_wait(bars + (B_WFULL + ws) * 8, wph);
      const uint64_t dw = dw0 + ws * (W_BYTES / 16);
      wg_fence();
      ss160<0, 0>(acc, dp + c5 * 256, dw, 1);
      wg_commit();
      wg_wait<1>();
      if (tid == 0) {
        const int cprev = tau * 5 + c5 - 1;
        if (cprev <= 13) mbar_arrive(bars + (B_WEMPTY + wsp) * 8);
        if (cprev == 9) mbar_arrive_rem(mapa(bars + (B_PFREE + 2) * 8, CL == 8 ? half * 4 + ((j + 3) & 3) : rank));
        if (cprev == 14) mbar_arrive_rem(mapa(bars + (B_XFREE + wg) * 8, rank ^ (CL / 2)));
      }
      wg_fence();
      ss160<0, 0>(acc, dp + c5 * 256 + 2, dw + 2, 1);
      wg_commit();
      wg_wait<1>();
      wsp = ws;
      if (++ws == NWS) { ws = 0; wph ^= 1; }
    }
  }
  wg_wait<0>();
#pragma unroll
  for (int i = 0; i < 80; i++) asm volatile("" : "+f"(acc[i])::"memory");
  if (tid == 0 && wg == 0) PSTAMP(6);
  mbar_wait(bars + (B_XFREE + wg) * 8, 0);
  {
    const uint32_t xl = sb + OFF_SLOTB + wg * PHALF + tid * 16;
    const uint32_t xr = mapa(xl, rank ^ (CL / 2));
    const uint32_t xb = mapa(bars + (B_XFULL + wg) * 8, rank ^ (CL / 2));
#pragma unroll
    for (int i = 0; i < 5; i++) {
      uint32_t sv[4];
#pragma unroll
      for (int m = 0; m < 4; m++) {
        const int idx = 8 * i + 2 * m;
        float lo = half ? acc[idx] : acc[40 + idx], hi = half ? acc[idx + 1] : acc[41 + idx];
        sv[m] = pack_bf16(lo, hi);
      }
      st_async4(xr + i * 2048, sv[0], sv[1], sv[2], sv[3], xb);
    }
    mbar_wait(bars + (B_XFULL + wg) * 8, 0);
    const float sg = half ? -1.f : 1.f;
    const uint32_t ost = sb + OFF_SLOTB + wg * PHALF + 10240;
    const uint32_t oa = ost + (16 * w + (lane & 7) + 8 * ((lane >> 3) & 1)) * 160 + (lane >> 4) * 16;
#pragma unroll
    for (int i = 0; i < 5; i++) {
      uint4 rv = lds128(xl + i * 2048);
      const uint32_t* rr = (const uint32_t*)&rv;
      uint32_t ov[4];
#pragma unroll
      for (int m = 0; m < 4; m++) {
        const int idx = 8 * i + 2 * m;
        float lo = half ? acc[40 + idx] : acc[idx], hi = half ? acc[41 + idx] : acc[idx + 1];
        float rl = __uint_as_float(rr[m] << 16), rh = __uint_as_float(rr[m] & 0xffff0000u);
        ov[m] = pack_bf16(sg * (lo - rl), sg * (hi - rh));
      }
      asm volatile("stmatrix.sync.aligned.m8n8.x4.shared.b16 [%0], {%1,%2,%3,%4};" ::"r"(oa + i * 32), "r"(ov[0]), "r"(ov[1]), "r"(ov[2]), "r"(ov[3]) : "memory");
    }
    fence_async();
    __syncwarp();
    if (lane == 0) {
      tma_store2d(mOa, ost + w * 2560, j * 160 + half * 80, tt * 128 + wg * 64 + w * 16);
      bulk_commit();
      bulk_wait_read();
    }
  }
  if (tid == 0 && wg == 0) { PSTAMP(7); PGT(63); }
}

template <int CL>
__global__ void __launch_bounds__(512, 1)
fused_kernel(const __grid_constant__ CUtensorMap mCr, const __grid_constant__ CUtensorMap mCi, const __grid_constant__ CUtensorMap mX,
             const __grid_constant__ CUtensorMap mWr, const __grid_constant__ CUtensorMap mWi, const __grid_constant__ CUtensorMap mKin,
             const __grid_constant__ CUtensorMap mVin, const __grid_constant__ CUtensorMap mQ, const __grid_constant__ CUtensorMap mOa,
             const __grid_constant__ CUtensorMap mOb,
             const __grid_constant__ Params p) {
  extern __shared__ __align__(1024) unsigned char smem[];
  const uint32_t sb = smem_u32(smem);
  const uint32_t bars = sb + OFF_BAR;
  const int wg = __shfl_sync(0xffffffffu, threadIdx.x >> 7, 0);
  const int tid = threadIdx.x & 127, lane = threadIdx.x & 31;
  const int warp = __shfl_sync(0xffffffffu, tid >> 5, 0);
  uint32_t rank;
  asm("mov.u32 %0, %%cluster_ctarank;" : "=r"(rank));
  const int cid = blockIdx.x / CL;
  constexpr int SEGS = 8 / CL;
  bool gemm;
  int tt, half, j, oct0, noct;
  if (CL == 8) {
    asm volatile("griddepcontrol.launch_dependents;");
    gemm = true; tt = cid; half = rank >> 2; j = rank & 3; oct0 = 5 * cid; noct = 5;
  } else {
    const int ti = cid / 6, c6 = cid % 6;
    tt = p.nA + ti; half = rank; j = c6 & 3; gemm = c6 < 4;
    oct0 = 5 * tt + (c6 == 5 ? 3 : 0);
    noct = gemm ? 0 : (c6 == 4 ? 3 : 2);
  }
  const uint32_t ubase = CL == 8 ? sb + OFF_U : sb;
  if (threadIdx.x == 0) { PSTAMP(0); PGT(62); PZERO(1, 7); PZERO(44, 51); }
  if (threadIdx.x == 256) { PZERO(8, 9); PZERO(12, 43); }
  if (threadIdx.x == 384) PZERO(52, 61);

  if (threadIdx.x == 384) {
    if (sb & 1023) __trap();
    for (int i = 0; i < NSTG; i++) { mbar_init(bars + (B_FULL + i) * 8, 1); mbar_init(bars + (B_EMPTY + i) * 8, CL == 8 ? 10 : 4); }
    for (int i = 0; i < NWS; i++) { mbar_init(bars + (B_WFULL + i) * 8, 1); mbar_init(bars + (B_WEMPTY + i) * 8, 2); }
    asm volatile("fence.mbarrier_init.release.cluster;" ::: "memory");
  } else if (threadIdx.x == 416) {
    for (int i = 0; i < 3; i++) { mbar_init(bars + (B_PFREE + i) * 8, 2); mbar_init(bars + (B_OFREE + i) * 8, 8); }
    for (int i = 0; i < 2; i++) {
      mbar_init(bars + (B_STAGED + i) * 8, 4); mbar_init(bars + (B_XFREE + i) * 8, 1);
      mbar_init(bars + (B_XFULL + i) * 8, 1); mbar_expect_tx(bars + (B_XFULL + i) * 8, 10240);
    }
    asm volatile("fence.mbarrier_init.release.cluster;" ::: "memory");
  } else if (threadIdx.x >= 448 && threadIdx.x < 472) {
    const int i = threadIdx.x - 448;
    mbar_init(bars + (B_UFULL + i) * 8, 1); mbar_expect_tx(bars + (B_UFULL + i) * 8, 4096);
    asm volatile("fence.mbarrier_init.release.cluster;" ::: "memory");
  } else if (threadIdx.x >= 480 && threadIdx.x < 495) {
    const int i = threadIdx.x - 480;
    mbar_init(bars + (B_PFULL + i) * 8, 1); mbar_expect_tx(bars + (B_PFULL + i) * 8, 8192);
    asm volatile("fence.mbarrier_init.release.cluster;" ::: "memory");
  } else if (threadIdx.x >= 256 && threadIdx.x < 284) {
    const int i = threadIdx.x - 256;
    mbar_init(bars + (i < 8 ? B_KFULL + i : B_QFULL + i - 8) * 8, 1);
    asm volatile("fence.mbarrier_init.release.cluster;" ::: "memory");
  } else if (wg < 2 && noct > 0) {
    const int t = threadIdx.x;
    const int nsl = noct * SEGS;
    for (int i = t; i < nsl * 32; i += 256) sts128(ubase + (i >> 5) * USLOT + 4096 + (i & 31) * 16, 0, 0, 0, 0);
    if (t < 16) sts128(sb + OFF_K + (t >> 3) * KE_OFF + (t & 7) * 16, 0, 0, 0, 0);
    fence_async();
  }
  if (threadIdx.x == 384) PSTAMP(52);
  __syncwarp();
  cluster_arrive();
  if (threadIdx.x == 384) PSTAMP(54);

  Maps mp;
  mp.k = &mKin; mp.v = &mVin; mp.q = &mQ; mp.ob = &mOb;
  const int toct = 5 * tt, olo = oct0 - toct;
  if (wg < 2) {
    cluster_wait();
    if (threadIdx.x == 0) PSTAMP(1);
    if (gemm) {
      gemm_consumer<CL>(&mOa, sb, wg, tid, rank, half, j, tt);
    } else if (noct > 0) {
      const int wi = wg * 4 + warp;
      const uint32_t lb = sb + OFF_L2 + wi * LBUF, lbar = bars + (B_LFULL + wi) * 8;
      const uint32_t qb = sb + OFF_Q2 + wi * 4096, qbar = bars + (B_QFULL + wi) * 8;
      const int ntask = noct * SEGS;
      if (lane == 0) {
        p0_issue(mp, lb, lbar, toct * 8, rank * 1024 + wi * 32);
        mbar_expect_tx(qbar, 4096);
        tma2d(qb, mp.q, (oct0 + wi / SEGS) * 8, (rank * SEGS + wi % SEGS) * 256, qbar);
      }
      p0_warp<CL>(p, mp, sb, ubase, lb, lbar, toct, olo, noct, rank * 1024 + wi * 32, 256, 4, 256, rank * 1024 + 1024, lane);
#pragma unroll 1
      for (int t = wi; t < ntask; t += 8)
        conv_out<CL>(mp, sb, qb, qbar, t >> 3, oct0 + t / SEGS, t, rank * SEGS + t % SEGS, t + 8 < ntask ? oct0 + (t + 8) / SEGS : -1,
                     rank * SEGS + t % SEGS, lane);
      cluster_arrive(); cluster_wait();
    }
    if (threadIdx.x == 0) { PDUMP(0, 7); PDUMP(44, 51); PDUMP(62, 63); }
  } else if (wg == 2) {
    cluster_wait();
    if (CL == 8 && noct > 0) {
      const uint32_t lb = sb + OFF_OST + (warp & 1) * LBUF, lbar = bars + (B_LFULL + warp) * 8;
      if (lane == 0 && warp < 2) p0_issue(mp, lb, lbar, toct * 8, rank * 256 + warp * 32);
      p0_warp<CL>(p, mp, sb, ubase, lb, lbar, toct, 0, 5, rank * 256 + warp * 32, 128, 2, 64, rank * 256 + 256, lane);
    }
    if (tid == 0) PSTAMP(8);
    asm volatile("setmaxnreg.inc.sync.aligned.u32 136;");
    if (noct > 0) conv_main<CL>(p, sb, ubase, rank, oct0, noct, tid);
    if (tid == 0) { PSTAMP(9); PDUMP(8, 9); PDUMP(12, 43); }
  } else {
    asm volatile("setmaxnreg.dec.sync.aligned.u32 72;");
    if (warp == 0) {
      if (lane == 0) PSTAMP(55);
      cluster_wait();
      if (lane == 0) PSTAMP(56);
      if (lane == 0 && gemm) {
        const CUtensorMap* mC = half ? &mCi : &mCr;
        const CUtensorMap* mW = half ? &mWi : &mWr;
        int s = 0;
        uint32_t ph = 1;
#pragma unroll 1
        for (int k = 0; k < 32; k++) {
          if (k >= NSTG) mbar_wait(bars + (B_EMPTY + s) * 8, ph);
          const uint32_t fb = bars + (B_FULL + s) * 8, st = sb + s * STG_BYTES;
          mbar_expect_tx(fb, STG_BYTES);
          if (CL == 8) {
            tma2d_mc(st + j * 4096, mC, k * 64, tt * 128 + j * 32, fb, (uint16_t)(0xF << (4 * half)));
            tma3d_mc(st + A_BYTES + half * (B_BYTES / 2), &mX, 0, k * 64 + 32 * half, j * 5, fb, (uint16_t)(0x11 << j));
          } else {
            tma3d_mc(st + A_BYTES + half * (B_BYTES / 2), &mX, 0, k * 64 + 32 * half, j * 5, fb, (uint16_t)3);
#pragma unroll
            for (int i = 0; i < 4; i++) tma2d(st + i * 4096, mC, k * 64, tt * 128 + i * 32, fb);
          }
          if (++s == NSTG) { s = 0; ph ^= 1; }
          if (k == 0) PSTAMP(57);
          if (k == 4) PSTAMP(58);
        }
        int ws = 0;
        uint32_t wph = 1;
#pragma unroll 1
        for (int c = 0; c < 20; c++) {
          if (c == 0) mbar_wait(bars + (B_EMPTY + 2) * 8, 1);
          if (c == 2) mbar_wait(bars + (B_EMPTY + 3) * 8, 1);
          if (c >= NWS) mbar_wait(bars + (B_WEMPTY + ws) * 8, wph);
          const uint32_t fb = bars + (B_WFULL + ws) * 8;
          mbar_expect_tx(fb, W_BYTES);
          tma2d(sb + OFF_W + ws * W_BYTES, mW, ((j + c / 5) & 3) * 160 + (c % 5) * 32, j * 160, fb);
          if (++ws == NWS) { ws = 0; wph ^= 1; }
        }
      }
      if (lane == 0) PDUMP(52, 61);
    } else if (warp == 3) {
      cluster_wait();
      if (lane == 0 && gemm) {
        if (CL == 8) {
#pragma unroll 1
          for (int tau = 1; tau < 4; tau++) {
            mbar_wait(bars + (B_PFREE + tau - 1) * 8, 0);
            const uint32_t dst = half * 4 + ((j - tau) & 3);
            if (tau == 1) { mbar_wait(bars + B_STAGED * 8, 0); mbar_wait(bars + (B_STAGED + 1) * 8, 0); }
            const uint32_t rd = mapa(sb + (tau == 2 ? OFF_SLOTB : OFF_SLOTA), dst), rb = mapa(bars + (B_PFULL + (tau - 1) * 5) * 8, dst);
#pragma unroll
            for (int c = 0; c < 5; c++)
#pragma unroll
              for (int h = 0; h < 2; h++) bulk_s2s(rd + h * PHALF + c * 4096, sb + OFF_PST + h * PHALF + c * 4096, 4096, rb + c * 8);
          }
        } else {
          unsigned char* scr = g_pscr + (size_t)(tt * 8 + half * 4) * 40960;
          unsigned int* fl = g_flag + (tt * 8 + half * 4) * 4;
          mbar_wait(bars + B_STAGED * 8, 0);
          mbar_wait(bars + (B_STAGED + 1) * 8, 0);
          bulk_s2g(scr + j * 40960, sb + OFF_PST, 40960);
          asm volatile("cp.async.bulk.commit_group;" ::: "memory");
          asm volatile("cp.async.bulk.wait_group 0;" ::: "memory");
          asm volatile("fence.proxy.async;" ::: "memory");
          __threadfence();
          for (int tau = 1; tau < 4; tau++) asm volatile("st.release.gpu.global.u32 [%0], %1;" ::"l"(fl + j * 4 + tau), "r"(1u) : "memory");
#pragma unroll 1
          for (int tau = 1; tau < 4; tau++) {
            const int src = (j + tau) & 3;
            mbar_wait(bars + (B_PFREE + tau - 1) * 8, 0);
            unsigned int f, it = 0;
            while (true) {
              asm volatile("ld.acquire.gpu.global.u32 %0, [%1];" : "=r"(f) : "l"(fl + src * 4 + tau) : "memory");
              if (f) break;
              if (++it > (1u << 22)) __trap();
            }
            asm volatile("st.relaxed.gpu.global.u32 [%0], %1;" ::"l"(fl + src * 4 + tau), "r"(0u) : "memory");
            asm volatile("fence.proxy.async;" ::: "memory");
#pragma unroll
            for (int c = 0; c < 5; c++)
#pragma unroll
              for (int h = 0; h < 2; h++)
                bulk_g2s(sb + (tau == 2 ? OFF_SLOTB : OFF_SLOTA) + h * PHALF + c * 4096, scr + src * 40960 + h * PHALF + c * 4096, 4096,
                         bars + (B_PFULL + (tau - 1) * 5 + c) * 8);
          }
        }
      }
    } else if (warp == 2) {
      if (noct > 0) k_builder<CL>(p, sb, rank, oct0, noct, lane);
      else cluster_wait();
    } else {
      if (CL == 8 && noct > 0) {
        cluster_wait();
        const uint32_t qb = sb + OFF_OST + 8192, qbar = bars + B_QFULL * 8;
        mbar_wait(bars + B_UFULL * 8, 0);
        if (lane == 0) { mbar_expect_tx(qbar, 4096); tma2d(qb, mp.q, oct0 * 8, rank * 256, qbar); }
#pragma unroll 1
        for (int t = 0; t < 5; t++) conv_out<CL>(mp, sb, qb, qbar, t & 1, oct0 + t, t, rank, t < 4 ? oct0 + t + 1 : -1, rank, lane);
        if (lane == 0) { PSTAMP(10); PDUMP(10, 10); }
        cluster_arrive(); cluster_wait();
      } else {
        cluster_wait();
      }
    }
  }
}

typedef CUresult (*PFN_encodeTiled)(CUtensorMap*, CUtensorMapDataType, cuuint32_t, void*, const cuuint64_t*, const cuuint64_t*, const cuuint32_t*,
                                    const cuuint32_t*, CUtensorMapInterleave, CUtensorMapSwizzle, CUtensorMapL2promotion, CUtensorMapFloatOOBfill);

void make_map(PFN_encodeTiled enc, CUtensorMap* m, const void* ptr, int rank, const cuuint64_t* dims, const cuuint64_t* strides, const cuuint32_t* box,
              CUtensorMapSwizzle swz, CUtensorMapL2promotion prom) {
  cuuint32_t es[5] = {1, 1, 1, 1, 1};
  enc(m, CU_TENSOR_MAP_DATA_TYPE_BFLOAT16, rank, const_cast<void*>(ptr), dims, strides, box, es, CU_TENSOR_MAP_INTERLEAVE_NONE, swz, prom,
      CU_TENSOR_MAP_FLOAT_OOB_FILL_NONE);
}

}

extern "C" void kernel_launch(void* const* d_in, const int* in_sizes, int n_in, void* d_out, int out_size) {
  static PFN_encodeTiled enc = nullptr;
  static int nA = -1;
  cudaStream_t st = cudaStreamPerThread;
  cudaLaunchConfig_t cfg = {};
  cudaLaunchAttribute at[2];
  cfg.blockDim = dim3(512);
  cfg.dynamicSmemBytes = SMEM_BYTES;
  cfg.stream = st;
  cfg.attrs = at;
  at[0].id = cudaLaunchAttributeClusterDimension;
  at[0].val.clusterDim.y = 1;
  at[0].val.clusterDim.z = 1;
  if (nA < 0) {
    void* fn = nullptr;
    cudaDriverEntryPointQueryResult qr;
    cudaGetDriverEntryPoint("cuTensorMapEncodeTiled", &fn, cudaEnableDefault, &qr);
    enc = (PFN_encodeTiled)fn;
    cudaFuncSetAttribute(fused_kernel<8>, cudaFuncAttributeMaxDynamicSharedMemorySize, SMEM_BYTES);
    cudaFuncSetAttribute(fused_kernel<2>, cudaFuncAttributeMaxDynamicSharedMemorySize, SMEM_BYTES);
    int nc = 0;
    cfg.gridDim = dim3(128);
    at[0].val.clusterDim.x = 8;
    cfg.numAttrs = 1;
    if (cudaOccupancyMaxActiveClusters(&nc, fused_kernel<8>, &cfg) != cudaSuccess) nc = 0;
    nA = nc > 16 ? 16 : nc;
  }
  CUtensorMap mCr, mCi, mX, mWr, mWi, mKin, mVin, mQ, mOa, mOb;
  {
    cuuint64_t d[2] = {2048, 2048}, s[1] = {4096};
    cuuint32_t b[2] = {64, 32};
    make_map(enc, &mCr, d_in[1], 2, d, s, b, CU_TENSOR_MAP_SWIZZLE_128B, CU_TENSOR_MAP_L2_PROMOTION_L2_256B);
    make_map(enc, &mCi, d_in[2], 2, d, s, b, CU_TENSOR_MAP_SWIZZLE_128B, CU_TENSOR_MAP_L2_PROMOTION_L2_256B);
  }
  {
    cuuint64_t d[3] = {32, 2048, 20}, s[2] = {1280, 64};
    cuuint32_t b[3] = {32, 32, 5};
    make_map(enc, &mX, d_in[0], 3, d, s, b, CU_TENSOR_MAP_SWIZZLE_64B, CU_TENSOR_MAP_L2_PROMOTION_L2_128B);
  }
  {
    cuuint64_t d[2] = {640, 640}, s[1] = {1280};
    cuuint32_t b[2] = {32, 160};
    make_map(enc, &mWr, d_in[3], 2, d, s, b, CU_TENSOR_MAP_SWIZZLE_64B, CU_TENSOR_MAP_L2_PROMOTION_L2_128B);
    make_map(enc, &mWi, d_in[4], 2, d, s, b, CU_TENSOR_MAP_SWIZZLE_64B, CU_TENSOR_MAP_L2_PROMOTION_L2_128B);
  }
  {
    cuuint64_t d[3] = {640, 256, 8}, s[2] = {10240, 1280};
    cuuint32_t bk[3] = {40, 5, 8}, bv[3] = {40, 4, 8};
    make_map(enc, &mKin, d_in[6], 3, d, s, bk, CU_TENSOR_MAP_SWIZZLE_NONE, CU_TENSOR_MAP_L2_PROMOTION_L2_128B);
    make_map(enc, &mVin, d_in[7], 3, d, s, bv, CU_TENSOR_MAP_SWIZZLE_NONE, CU_TENSOR_MAP_L2_PROMOTION_L2_128B);
  }
  {
    cuuint64_t d[2] = {640, 2048}, s[1] = {1280}, d2[2] = {1280, 2048}, s2[1] = {2560};
    cuuint32_t b[2] = {8, 256}, ba[2] = {80, 16};
    make_map(enc, &mQ, d_in[5], 2, d, s, b, CU_TENSOR_MAP_SWIZZLE_NONE, CU_TENSOR_MAP_L2_PROMOTION_L2_128B);
    make_map(enc, &mOb, d_out, 2, d2, s2, b, CU_TENSOR_MAP_SWIZZLE_NONE, CU_TENSOR_MAP_L2_PROMOTION_NONE);
    make_map(enc, &mOa, d_out, 2, d2, s2, ba, CU_TENSOR_MAP_SWIZZLE_NONE, CU_TENSOR_MAP_L2_PROMOTION_NONE);
  }
  Params p;
  p.q = (const bf16*)d_in[5]; p.k = (const bf16*)d_in[6]; p.v = (const bf16*)d_in[7];
  p.shift_k = (const bf16*)d_in[8]; p.ssm_k = (const bf16*)d_in[9]; p.ssm_D = (const bf16*)d_in[10];
  p.out = (bf16*)d_out; p.nA = nA;
  if (nA > 0) {
    cfg.gridDim = dim3(nA * 8);
    at[0].val.clusterDim.x = 8;
    cfg.numAttrs = 1;
    cudaLaunchKernelEx(&cfg, fused_kernel<8>, mCr, mCi, mX, mWr, mWi, mKin, mVin, mQ, mOa, mOb, p);
  }
  if (nA < 16) {
    cfg.gridDim = dim3((16 - nA) * 12);
    at[0].val.clusterDim.x = 2;
    at[1].id = cudaLaunchAttributeProgrammaticStreamSerialization;
    at[1].val.programmaticStreamSerializationAllowed = 1;
    cfg.numAttrs = nA > 0 ? 2 : 1;
    cudaLaunchKernelEx(&cfg, fused_kernel<2>, mCr, mCi, mX, mWr, mWi, mKin, mVin, mQ, mOa, mOb, p);
  }
}
```

```cpp
#include <cuda_runtime.h>
#include <cuda.h>
#include <cuda_bf16.h>
#include <stdint.h>

#define P0E 4
#define XP 0
namespace {

typedef __nv_bfloat16 bf16;
typedef __nv_bfloat162 bf162;

constexpr int NSTG = 5, A_BYTES = 16384, B_BYTES = 20480, STG_BYTES = A_BYTES + B_BYTES;
constexpr int RING = NSTG * STG_BYTES;
constexpr int OFF_W = 73728, W_BYTES = 10240;
constexpr int OFF_SPX = 65536, OFF_SPY = 176128, OFF_XCH = 73728;
constexpr int USLOT = 4608;
constexpr int OFF_U = RING;
constexpr int OFF_K = OFF_U + 5 * USLOT;
constexpr int KE_OFF = 4288, KBUF = 8576;
constexpr int OFF_X = OFF_K + KBUF;
constexpr int OFF_OST = OFF_X + 2048;
constexpr int OFF_BAR = OFF_OST + 3 * 4096;
constexpr int SMEM_BYTES = OFF_BAR + 1024 + 512;
constexpr int LKP = 5376, LKB = 5280, LVP = 5120, LV_OFF = 4 * LKP, LSET = LV_OFF + 4 * LVP, LSET_TX = 4 * (LKB + LVP);
constexpr int OFF_LA = 3 * STG_BYTES;
constexpr int OFF_OST2 = 57344, OFF_L2 = OFF_OST2 + 12 * 4096, OFF_K2 = OFF_L2 + 2 * LSET, OFF_X2 = OFF_K2 + 3 * KBUF;
static_assert(OFF_X2 + 3 * 2048 <= OFF_BAR, "smem");

enum { B_FULL = 0, B_C0FREE = 5, B_XFULL = 6, B_EMPTY = 8, B_WEMPTY = 16, B_DRAIN = 22, B_XFREE = 23, B_PFREE = 24, B_STAGED = 32, B_OFREE = 35,
       B_PFULL = 40, B_QFULL8 = 60, B_WFULL = 64, B_OFULL8 = 74, B_KBAR = 80, B_UFULL = 104, B_OFULL2 = 116, B_QFULL2 = B_PFULL, B_LFULL = B_FULL };

struct Params {
  const bf16 *x, *cr, *ci, *shift_k, *ssm_k, *ssm_D;
  int nA;
};

__device__ __align__(1024) unsigned char g_pscr[16 * 8 * 40960];
__device__ unsigned int g_flag[16 * 8 * 4];
#define PSTAMP(i)
#define PGT(i)
#define PZERO(lo, hi)
#define PDUMP(lo, hi)

__device__ __forceinline__ uint32_t smem_u32(const void* p) { return (uint32_t)__cvta_generic_to_shared(p); }
__device__ __forceinline__ uint64_t make_desc(uint32_t saddr, uint32_t lbo, uint32_t sbo, uint32_t swz) {
  return (uint64_t)((saddr & 0x3FFFF) >> 4) | ((uint64_t)(lbo >> 4) << 16) | ((uint64_t)(sbo >> 4) << 32) | ((uint64_t)swz << 62);
}
__device__ __forceinline__ void mbar_init(uint32_t bar, uint32_t cnt) { asm volatile("mbarrier.init.shared::cta.b64 [%0], %1;" ::"r"(bar), "r"(cnt) : "memory"); }
__device__ __forceinline__ void mbar_expect_tx(uint32_t bar, uint32_t bytes) { asm volatile("mbarrier.arrive.expect_tx.shared::cta.b64 _, [%0], %1;" ::"r"(bar), "r"(bytes) : "memory"); }
__device__ __forceinline__ void mbar_arrive(uint32_t bar) { asm volatile("mbarrier.arrive.shared::cta.b64 _, [%0];" ::"r"(bar) : "memory"); }
__device__ __forceinline__ uint32_t mapa(uint32_t a, uint32_t cta) { uint32_t r; asm("mapa.shared::cluster.u32 %0, %1, %2;" : "=r"(r) : "r"(a), "r"(cta)); return r; }
__device__ __forceinline__ void mbar_arrive_rem(uint32_t rbar) { asm volatile("mbarrier.arrive.shared::cluster.b64 _, [%0];" ::"r"(rbar) : "memory"); }
__device__ __forceinline__ void mbar_wait(uint32_t bar, uint32_t parity) {
  asm volatile("{\n.reg .pred p;\n.reg .u32 c;\nmov.u32 c, 0;\nLW:\nmbarrier.try_wait.parity.shared::cta.b64 p, [%0], %1;\n@p bra LD;\n"
               "add.u32 c, c, 1;\nsetp.lt.u32 p, c, 4194304;\n@p bra LW;\ntrap;\nLD:\n}\n" ::"r"(bar), "r"(parity) : "memory");
}
__device__ __forceinline__ void tma2d(uint32_t dst, const CUtensorMap* m, int c0, int c1, uint32_t bar) {
  asm volatile("cp.async.bulk.tensor.2d.shared::cluster.global.mbarrier::complete_tx::bytes [%0], [%1, {%3,%4}], [%2];" ::"r"(dst), "l"(m), "r"(bar), "r"(c0), "r"(c1) : "memory");
}
__device__ __forceinline__ void tma2d_mc(uint32_t dst, const CUtensorMap* m, int c0, int c1, uint32_t bar, uint16_t mask) {
  asm volatile("cp.async.bulk.tensor.2d.shared::cluster.global.mbarrier::complete_tx::bytes.multicast::cluster [%0], [%1, {%3,%4}], [%2], %5;" ::"r"(dst), "l"(m), "r"(bar), "r"(c0), "r"(c1), "h"(mask) : "memory");
}
__device__ __forceinline__ void tma3d_mc(uint32_t dst, const CUtensorMap* m, int c0, int c1, int c2, uint32_t bar, uint16_t mask) {
  asm volatile("cp.async.bulk.tensor.3d.shared::cluster.global.mbarrier::complete_tx::bytes.multicast::cluster [%0], [%1, {%3,%4,%5}], [%2], %6;" ::"r"(dst), "l"(m), "r"(bar), "r"(c0), "r"(c1), "r"(c2), "h"(mask) : "memory");
}
__device__ __forceinline__ void tma3d(uint32_t dst, const CUtensorMap* m, int c0, int c1, int c2, uint32_t bar) {
  asm volatile("cp.async.bulk.tensor.3d.shared::cluster.global.mbarrier::complete_tx::bytes [%0], [%1, {%3,%4,%5}], [%2];" ::"r"(dst), "l"(m), "r"(bar), "r"(c0), "r"(c1), "r"(c2) : "memory");
}
__device__ __forceinline__ void tma_store2d(const CUtensorMap* m, uint32_t src, int c0, int c1) {
  asm volatile("cp.async.bulk.tensor.2d.global.shared::cta.bulk_group [%0, {%2,%3}], [%1];" ::"l"(m), "r"(src), "r"(c0), "r"(c1) : "memory");
}
__device__ __forceinline__ void bulk_commit() { asm volatile("cp.async.bulk.commit_group;" ::: "memory"); }
__device__ __forceinline__ void bulk_wait_read() { asm volatile("cp.async.bulk.wait_group.read 0;" ::: "memory"); }
__device__ __forceinline__ void bulk_g2s(uint32_t dst, const void* src, uint32_t bytes, uint32_t bar) {
  asm volatile("cp.async.bulk.shared::cluster.global.mbarrier::complete_tx::bytes [%0], [%1], %2, [%3];" ::"r"(dst), "l"(src), "r"(bytes), "r"(bar) : "memory");
}
__device__ __forceinline__ void bulk_g2s_mc(uint32_t dst, const void* src, uint32_t bytes, uint32_t bar, uint16_t mask) {
  asm volatile("cp.async.bulk.shared::cluster.global.mbarrier::complete_tx::bytes.multicast::cluster [%0], [%1], %2, [%3], %4;" ::"r"(dst), "l"(src), "r"(bytes), "r"(bar), "h"(mask) : "memory");
}
template <int N> __device__ __forceinline__ void bulk_wait() { asm volatile("cp.async.bulk.wait_group %0;" ::"n"(N) : "memory"); }
__device__ __forceinline__ void mbar_arrive_n(uint32_t bar, uint32_t n) { asm volatile("mbarrier.arrive.shared::cta.b64 _, [%0], %1;" ::"r"(bar), "r"(n) : "memory"); }
__device__ __forceinline__ void pf_l2(const void* p) { asm volatile("prefetch.global.L2 [%0];" ::"l"(p)); }
__device__ __forceinline__ void pf_map(const CUtensorMap* m) { asm volatile("prefetch.tensormap [%0];" ::"l"(m) : "memory"); }
__device__ __forceinline__ void stsm4(uint32_t a, uint32_t r0, uint32_t r1, uint32_t r2, uint32_t r3) {
  asm volatile("stmatrix.sync.aligned.m8n8.x4.shared.b16 [%0], {%1,%2,%3,%4};" ::"r"(a), "r"(r0), "r"(r1), "r"(r2), "r"(r3) : "memory");
}
__device__ __forceinline__ void bulk_s2s(uint32_t rdst, uint32_t src, uint32_t bytes, uint32_t rbar) {
  asm volatile("cp.async.bulk.shared::cluster.shared::cta.mbarrier::complete_tx::bytes [%0], [%1], %2, [%3];" ::"r"(rdst), "r"(src), "r"(bytes), "r"(rbar) : "memory");
}
__device__ __forceinline__ void bulk_s2g(void* dst, uint32_t src, uint32_t bytes) {
  asm volatile("cp.async.bulk.global.shared::cta.bulk_group [%0], [%1], %2;" ::"l"(dst), "r"(src), "r"(bytes) : "memory");
}
__device__ __forceinline__ void st_async4(uint32_t ra, uint32_t a, uint32_t b, uint32_t c, uint32_t d, uint32_t rbar) {
  asm volatile("st.async.weak.shared::cluster.mbarrier::complete_tx::bytes.v4.b32 [%0], {%1,%2,%3,%4}, [%5];" ::"r"(ra), "r"(a), "r"(b), "r"(c), "r"(d), "r"(rbar) : "memory");
}
__device__ __forceinline__ void st_async2(uint32_t ra, uint32_t a, uint32_t b, uint32_t rbar) {
  asm volatile("st.async.weak.shared::cluster.mbarrier::complete_tx::bytes.v2.b32 [%0], {%1,%2}, [%3];" ::"r"(ra), "r"(a), "r"(b), "r"(rbar) : "memory");
}
__device__ __forceinline__ uint32_t lds32(uint32_t a) { uint32_t v; asm volatile("ld.shared.u32 %0, [%1];" : "=r"(v) : "r"(a)); return v; }
__device__ __forceinline__ uint4 lds128(uint32_t a) { uint4 v; asm volatile("ld.shared.v4.u32 {%0,%1,%2,%3}, [%4];" : "=r"(v.x), "=r"(v.y), "=r"(v.z), "=r"(v.w) : "r"(a) : "memory"); return v; }
__device__ __forceinline__ void sts128(uint32_t a, uint32_t x, uint32_t y, uint32_t z, uint32_t w) { asm volatile("st.shared.v4.u32 [%0], {%1,%2,%3,%4};" ::"r"(a), "r"(x), "r"(y), "r"(z), "r"(w) : "memory"); }
__device__ __forceinline__ uint4 ldg128(const void* p) { uint4 v; asm volatile("ld.global.nc.L1::no_allocate.v4.u32 {%0,%1,%2,%3}, [%4];" : "=r"(v.x), "=r"(v.y), "=r"(v.z), "=r"(v.w) : "l"(p)); return v; }
__device__ __forceinline__ uint4 ldg128c(const void* p) { uint4 v; asm volatile("ld.global.nc.v4.u32 {%0,%1,%2,%3}, [%4];" : "=r"(v.x), "=r"(v.y), "=r"(v.z), "=r"(v.w) : "l"(p)); return v; }
__device__ __forceinline__ uint32_t pack_bf16(float lo, float hi) { uint32_t r; asm("cvt.rn.bf16x2.f32 %0, %1, %2;" : "=r"(r) : "f"(hi), "f"(lo)); return r; }
__device__ __forceinline__ uint32_t bmul(uint32_t a, uint32_t b) { uint32_t r; asm("mul.rn.bf16x2 %0, %1, %2;" : "=r"(r) : "r"(a), "r"(b)); return r; }
__device__ __forceinline__ uint32_t badd(uint32_t a, uint32_t b) { uint32_t r; asm("add.rn.bf16x2 %0, %1, %2;" : "=r"(r) : "r"(a), "r"(b)); return r; }
__device__ __forceinline__ uint32_t prmt(uint32_t a, uint32_t b, uint32_t s) { uint32_t r; asm("prmt.b32 %0, %1, %2, %3;" : "=r"(r) : "r"(a), "r"(b), "r"(s)); return r; }
__device__ __forceinline__ void fence_async() { asm volatile("fence.proxy.async.shared::cta;" ::: "memory"); }
__device__ __forceinline__ void wg_fence() { asm volatile("wgmma.fence.sync.aligned;" ::: "memory"); }
__device__ __forceinline__ void wg_commit() { asm volatile("wgmma.commit_group.sync.aligned;" ::: "memory"); }
template <int N> __device__ __forceinline__ void wg_wait() { asm volatile("wgmma.wait_group.sync.aligned %0;" ::"n"(N) : "memory"); }
__device__ __forceinline__ void bar_sync(int id, int n) { asm volatile("bar.sync %0, %1;" ::"r"(id), "r"(n) : "memory"); }
__device__ __forceinline__ void cluster_arrive() { asm volatile("barrier.cluster.arrive.relaxed.aligned;" ::: "memory"); }
__device__ __forceinline__ void cluster_wait() { asm volatile("barrier.cluster.wait.acquire.aligned;" ::: "memory"); }

template<int TB,int O,int NA> __device__ __forceinline__ void ss160(float (&c)[NA], uint64_t da, uint64_t db, int sd){
 asm volatile("{\n.reg .pred p;\nsetp.ne.b32 p, %82, 0;\nwgmma.mma_async.sync.aligned.m64n160k16.f32.bf16.bf16 {%0,%1,%2,%3,%4,%5,%6,%7,%8,%9,%10,%11,%12,%13,%14,%15,%16,%17,%18,%19,%20,%21,%22,%23,%24,%25,%26,%27,%28,%29,%30,%31,%32,%33,%34,%35,%36,%37,%38,%39,%40,%41,%42,%43,%44,%45,%46,%47,%48,%49,%50,%51,%52,%53,%54,%55,%56,%57,%58,%59,%60,%61,%62,%63,%64,%65,%66,%67,%68,%69,%70,%71,%72,%73,%74,%75,%76,%77,%78,%79},%80,%81,p,1,1,0,%83;\n}\n"
  : "+f"(c[O+0]),"+f"(c[O+1]),"+f"(c[O+2]),"+f"(c[O+3]),"+f"(c[O+4]),"+f"(c[O+5]),"+f"(c[O+6]),"+f"(c[O+7]),"+f"(c[O+8]),"+f"(c[O+9]),"+f"(c[O+10]),"+f"(c[O+11]),"+f"(c[O+12]),"+f"(c[O+13]),"+f"(c[O+14]),"+f"(c[O+15]),"+f"(c[O+16]),"+f"(c[O+17]),"+f"(c[O+18]),"+f"(c[O+19]),"+f"(c[O+20]),"+f"(c[O+21]),"+f"(c[O+22]),"+f"(c[O+23]),"+f"(c[O+24]),"+f"(c[O+25]),"+f"(c[O+26]),"+f"(c[O+27]),"+f"(c[O+28]),"+f"(c[O+29]),"+f"(c[O+30]),"+f"(c[O+31]),"+f"(c[O+32]),"+f"(c[O+33]),"+f"(c[O+34]),"+f"(c[O+35]),"+f"(c[O+36]),"+f"(c[O+37]),"+f"(c[O+38]),"+f"(c[O+39]),"+f"(c[O+40]),"+f"(c[O+41]),"+f"(c[O+42]),"+f"(c[O+43]),"+f"(c[O+44]),"+f"(c[O+45]),"+f"(c[O+46]),"+f"(c[O+47]),"+f"(c[O+48]),"+f"(c[O+49]),"+f"(c[O+50]),"+f"(c[O+51]),"+f"(c[O+52]),"+f"(c[O+53]),"+f"(c[O+54]),"+f"(c[O+55]),"+f"(c[O+56]),"+f"(c[O+57]),"+f"(c[O+58]),"+f"(c[O+59]),"+f"(c[O+60]),"+f"(c[O+61]),"+f"(c[O+62]),"+f"(c[O+63]),"+f"(c[O+64]),"+f"(c[O+65]),"+f"(c[O+66]),"+f"(c[O+67]),"+f"(c[O+68]),"+f"(c[O+69]),"+f"(c[O+70]),"+f"(c[O+71]),"+f"(c[O+72]),"+f"(c[O+73]),"+f"(c[O+74]),"+f"(c[O+75]),"+f"(c[O+76]),"+f"(c[O+77]),"+f"(c[O+78]),"+f"(c[O+79])
  : "l"(da),"l"(db),"r"(sd),"n"(TB));
}
template<int TB,int O,int NA> __device__ __forceinline__ void ss80(float (&c)[NA], uint64_t da, uint64_t db, int sd){
 asm volatile("{\n.reg .pred p;\nsetp.ne.b32 p, %42, 0;\nwgmma.mma_async.sync.aligned.m64n80k16.f32.bf16.bf16 {%0,%1,%2,%3,%4,%5,%6,%7,%8,%9,%10,%11,%12,%13,%14,%15,%16,%17,%18,%19,%20,%21,%22,%23,%24,%25,%26,%27,%28,%29,%30,%31,%32,%33,%34,%35,%36,%37,%38,%39},%40,%41,p,1,1,0,%43;\n}\n"
  : "+f"(c[O+0]),"+f"(c[O+1]),"+f"(c[O+2]),"+f"(c[O+3]),"+f"(c[O+4]),"+f"(c[O+5]),"+f"(c[O+6]),"+f"(c[O+7]),"+f"(c[O+8]),"+f"(c[O+9]),"+f"(c[O+10]),"+f"(c[O+11]),"+f"(c[O+12]),"+f"(c[O+13]),"+f"(c[O+14]),"+f"(c[O+15]),"+f"(c[O+16]),"+f"(c[O+17]),"+f"(c[O+18]),"+f"(c[O+19]),"+f"(c[O+20]),"+f"(c[O+21]),"+f"(c[O+22]),"+f"(c[O+23]),"+f"(c[O+24]),"+f"(c[O+25]),"+f"(c[O+26]),"+f"(c[O+27]),"+f"(c[O+28]),"+f"(c[O+29]),"+f"(c[O+30]),"+f"(c[O+31]),"+f"(c[O+32]),"+f"(c[O+33]),"+f"(c[O+34]),"+f"(c[O+35]),"+f"(c[O+36]),"+f"(c[O+37]),"+f"(c[O+38]),"+f"(c[O+39])
  : "l"(da),"l"(db),"r"(sd),"n"(TB));
}
template<int N> struct RS;
template<> struct RS<160>{ static __device__ __forceinline__ void run(float (&c)[80], const uint32_t* a, uint64_t db, int sd){
 asm volatile("{\n.reg .pred p;\nsetp.ne.b32 p, %85, 0;\nwgmma.mma_async.sync.aligned.m64n160k16.f32.bf16.bf16 {%0,%1,%2,%3,%4,%5,%6,%7,%8,%9,%10,%11,%12,%13,%14,%15,%16,%17,%18,%19,%20,%21,%22,%23,%24,%25,%26,%27,%28,%29,%30,%31,%32,%33,%34,%35,%36,%37,%38,%39,%40,%41,%42,%43,%44,%45,%46,%47,%48,%49,%50,%51,%52,%53,%54,%55,%56,%57,%58,%59,%60,%61,%62,%63,%64,%65,%66,%67,%68,%69,%70,%71,%72,%73,%74,%75,%76,%77,%78,%79},{%80,%81,%82,%83},%84,p,1,1,0;\n}\n"
  : "+f"(c[0]),"+f"(c[1]),"+f"(c[2]),"+f"(c[3]),"+f"(c[4]),"+f"(c[5]),"+f"(c[6]),"+f"(c[7]),"+f"(c[8]),"+f"(c[9]),"+f"(c[10]),"+f"(c[11]),"+f"(c[12]),"+f"(c[13]),"+f"(c[14]),"+f"(c[15]),"+f"(c[16]),"+f"(c[17]),"+f"(c[18]),"+f"(c[19]),"+f"(c[20]),"+f"(c[21]),"+f"(c[22]),"+f"(c[23]),"+f"(c[24]),"+f"(c[25]),"+f"(c[26]),"+f"(c[27]),"+f"(c[28]),"+f"(c[29]),"+f"(c[30]),"+f"(c[31]),"+f"(c[32]),"+f"(c[33]),"+f"(c[34]),"+f"(c[35]),"+f"(c[36]),"+f"(c[37]),"+f"(c[38]),"+f"(c[39]),"+f"(c[40]),"+f"(c[41]),"+f"(c[42]),"+f"(c[43]),"+f"(c[44]),"+f"(c[45]),"+f"(c[46]),"+f"(c[47]),"+f"(c[48]),"+f"(c[49]),"+f"(c[50]),"+f"(c[51]),"+f"(c[52]),"+f"(c[53]),"+f"(c[54]),"+f"(c[55]),"+f"(c[56]),"+f"(c[57]),"+f"(c[58]),"+f"(c[59]),"+f"(c[60]),"+f"(c[61]),"+f"(c[62]),"+f"(c[63]),"+f"(c[64]),"+f"(c[65]),"+f"(c[66]),"+f"(c[67]),"+f"(c[68]),"+f"(c[69]),"+f"(c[70]),"+f"(c[71]),"+f"(c[72]),"+f"(c[73]),"+f"(c[74]),"+f"(c[75]),"+f"(c[76]),"+f"(c[77]),"+f"(c[78]),"+f"(c[79])
  : "r"(a[0]),"r"(a[1]),"r"(a[2]),"r"(a[3]),"l"(db),"r"(sd));
}
 static __device__ __forceinline__ void first(float (&c)[80], const uint32_t* a, uint64_t db){
 asm volatile("{\n.reg .pred p;\nsetp.ne.b32 p, 0, 0;\nwgmma.mma_async.sync.aligned.m64n160k16.f32.bf16.bf16 {%0,%1,%2,%3,%4,%5,%6,%7,%8,%9,%10,%11,%12,%13,%14,%15,%16,%17,%18,%19,%20,%21,%22,%23,%24,%25,%26,%27,%28,%29,%30,%31,%32,%33,%34,%35,%36,%37,%38,%39,%40,%41,%42,%43,%44,%45,%46,%47,%48,%49,%50,%51,%52,%53,%54,%55,%56,%57,%58,%59,%60,%61,%62,%63,%64,%65,%66,%67,%68,%69,%70,%71,%72,%73,%74,%75,%76,%77,%78,%79},{%80,%81,%82,%83},%84,p,1,1,0;\n}\n"
  : "=f"(c[0]),"=f"(c[1]),"=f"(c[2]),"=f"(c[3]),"=f"(c[4]),"=f"(c[5]),"=f"(c[6]),"=f"(c[7]),"=f"(c[8]),"=f"(c[9]),"=f"(c[10]),"=f"(c[11]),"=f"(c[12]),"=f"(c[13]),"=f"(c[14]),"=f"(c[15]),"=f"(c[16]),"=f"(c[17]),"=f"(c[18]),"=f"(c[19]),"=f"(c[20]),"=f"(c[21]),"=f"(c[22]),"=f"(c[23]),"=f"(c[24]),"=f"(c[25]),"=f"(c[26]),"=f"(c[27]),"=f"(c[28]),"=f"(c[29]),"=f"(c[30]),"=f"(c[31]),"=f"(c[32]),"=f"(c[33]),"=f"(c[34]),"=f"(c[35]),"=f"(c[36]),"=f"(c[37]),"=f"(c[38]),"=f"(c[39]),"=f"(c[40]),"=f"(c[41]),"=f"(c[42]),"=f"(c[43]),"=f"(c[44]),"=f"(c[45]),"=f"(c[46]),"=f"(c[47]),"=f"(c[48]),"=f"(c[49]),"=f"(c[50]),"=f"(c[51]),"=f"(c[52]),"=f"(c[53]),"=f"(c[54]),"=f"(c[55]),"=f"(c[56]),"=f"(c[57]),"=f"(c[58]),"=f"(c[59]),"=f"(c[60]),"=f"(c[61]),"=f"(c[62]),"=f"(c[63]),"=f"(c[64]),"=f"(c[65]),"=f"(c[66]),"=f"(c[67]),"=f"(c[68]),"=f"(c[69]),"=f"(c[70]),"=f"(c[71]),"=f"(c[72]),"=f"(c[73]),"=f"(c[74]),"=f"(c[75]),"=f"(c[76]),"=f"(c[77]),"=f"(c[78]),"=f"(c[79])
  : "r"(a[0]),"r"(a[1]),"r"(a[2]),"r"(a[3]),"l"(db));
}
};
template<> struct RS<16>{ static __device__ __forceinline__ void run(float (&c)[64], const uint32_t* a, uint64_t db, int sd){
 asm volatile("{\n.reg .pred p;\nsetp.ne.b32 p, %13, 0;\nwgmma.mma_async.sync.aligned.m64n16k16.f32.bf16.bf16 {%0,%1,%2,%3,%4,%5,%6,%7},{%8,%9,%10,%11},%12,p,1,1,0;\n}\n"
  : "+f"(c[0]),"+f"(c[1]),"+f"(c[2]),"+f"(c[3]),"+f"(c[4]),"+f"(c[5]),"+f"(c[6]),"+f"(c[7])
  : "r"(a[0]),"r"(a[1]),"r"(a[2]),"r"(a[3]),"l"(db),"r"(sd));
}
};
template<> struct RS<32>{ static __device__ __forceinline__ void run(float (&c)[64], const uint32_t* a, uint64_t db, int sd){
 asm volatile("{\n.reg .pred p;\nsetp.ne.b32 p, %21, 0;\nwgmma.mma_async.sync.aligned.m64n32k16.f32.bf16.bf16 {%0,%1,%2,%3,%4,%5,%6,%7,%8,%9,%10,%11,%12,%13,%14,%15},{%16,%17,%18,%19},%20,p,1,1,0;\n}\n"
  : "+f"(c[0]),"+f"(c[1]),"+f"(c[2]),"+f"(c[3]),"+f"(c[4]),"+f"(c[5]),"+f"(c[6]),"+f"(c[7]),"+f"(c[8]),"+f"(c[9]),"+f"(c[10]),"+f"(c[11]),"+f"(c[12]),"+f"(c[13]),"+f"(c[14]),"+f"(c[15])
  : "r"(a[0]),"r"(a[1]),"r"(a[2]),"r"(a[3]),"l"(db),"r"(sd));
}
};
template<> struct RS<48>{ static __device__ __forceinline__ void run(float (&c)[64], const uint32_t* a, uint64_t db, int sd){
 asm volatile("{\n.reg .pred p;\nsetp.ne.b32 p, %29, 0;\nwgmma.mma_async.sync.aligned.m64n48k16.f32.bf16.bf16 {%0,%1,%2,%3,%4,%5,%6,%7,%8,%9,%10,%11,%12,%13,%14,%15,%16,%17,%18,%19,%20,%21,%22,%23},{%24,%25,%26,%27},%28,p,1,1,0;\n}\n"
  : "+f"(c[0]),"+f"(c[1]),"+f"(c[2]),"+f"(c[3]),"+f"(c[4]),"+f"(c[5]),"+f"(c[6]),"+f"(c[7]),"+f"(c[8]),"+f"(c[9]),"+f"(c[10]),"+f"(c[11]),"+f"(c[12]),"+f"(c[13]),"+f"(c[14]),"+f"(c[15]),"+f"(c[16]),"+f"(c[17]),"+f"(c[18]),"+f"(c[19]),"+f"(c[20]),"+f"(c[21]),"+f"(c[22]),"+f"(c[23])
  : "r"(a[0]),"r"(a[1]),"r"(a[2]),"r"(a[3]),"l"(db),"r"(sd));
}
};
template<> struct RS<64>{ static __device__ __forceinline__ void run(float (&c)[64], const uint32_t* a, uint64_t db, int sd){
 asm volatile("{\n.reg .pred p;\nsetp.ne.b32 p, %37, 0;\nwgmma.mma_async.sync.aligned.m64n64k16.f32.bf16.bf16 {%0,%1,%2,%3,%4,%5,%6,%7,%8,%9,%10,%11,%12,%13,%14,%15,%16,%17,%18,%19,%20,%21,%22,%23,%24,%25,%26,%27,%28,%29,%30,%31},{%32,%33,%34,%35},%36,p,1,1,0;\n}\n"
  : "+f"(c[0]),"+f"(c[1]),"+f"(c[2]),"+f"(c[3]),"+f"(c[4]),"+f"(c[5]),"+f"(c[6]),"+f"(c[7]),"+f"(c[8]),"+f"(c[9]),"+f"(c[10]),"+f"(c[11]),"+f"(c[12]),"+f"(c[13]),"+f"(c[14]),"+f"(c[15]),"+f"(c[16]),"+f"(c[17]),"+f"(c[18]),"+f"(c[19]),"+f"(c[20]),"+f"(c[21]),"+f"(c[22]),"+f"(c[23]),"+f"(c[24]),"+f"(c[25]),"+f"(c[26]),"+f"(c[27]),"+f"(c[28]),"+f"(c[29]),"+f"(c[30]),"+f"(c[31])
  : "r"(a[0]),"r"(a[1]),"r"(a[2]),"r"(a[3]),"l"(db),"r"(sd));
}
};
template<> struct RS<80>{ static __device__ __forceinline__ void run(float (&c)[64], const uint32_t* a, uint64_t db, int sd){
 asm volatile("{\n.reg .pred p;\nsetp.ne.b32 p, %45, 0;\nwgmma.mma_async.sync.aligned.m64n80k16.f32.bf16.bf16 {%0,%1,%2,%3,%4,%5,%6,%7,%8,%9,%10,%11,%12,%13,%14,%15,%16,%17,%18,%19,%20,%21,%22,%23,%24,%25,%26,%27,%28,%29,%30,%31,%32,%33,%34,%35,%36,%37,%38,%39},{%40,%41,%42,%43},%44,p,1,1,0;\n}\n"
  : "+f"(c[0]),"+f"(c[1]),"+f"(c[2]),"+f"(c[3]),"+f"(c[4]),"+f"(c[5]),"+f"(c[6]),"+f"(c[7]),"+f"(c[8]),"+f"(c[9]),"+f"(c[10]),"+f"(c[11]),"+f"(c[12]),"+f"(c[13]),"+f"(c[14]),"+f"(c[15]),"+f"(c[16]),"+f"(c[17]),"+f"(c[18]),"+f"(c[19]),"+f"(c[20]),"+f"(c[21]),"+f"(c[22]),"+f"(c[23]),"+f"(c[24]),"+f"(c[25]),"+f"(c[26]),"+f"(c[27]),"+f"(c[28]),"+f"(c[29]),"+f"(c[30]),"+f"(c[31]),"+f"(c[32]),"+f"(c[33]),"+f"(c[34]),"+f"(c[35]),"+f"(c[36]),"+f"(c[37]),"+f"(c[38]),"+f"(c[39])
  : "r"(a[0]),"r"(a[1]),"r"(a[2]),"r"(a[3]),"l"(db),"r"(sd));
}
};
template<> struct RS<96>{ static __device__ __forceinline__ void run(float (&c)[64], const uint32_t* a, uint64_t db, int sd){
 asm volatile("{\n.reg .pred p;\nsetp.ne.b32 p, %53, 0;\nwgmma.mma_async.sync.aligned.m64n96k16.f32.bf16.bf16 {%0,%1,%2,%3,%4,%5,%6,%7,%8,%9,%10,%11,%12,%13,%14,%15,%16,%17,%18,%19,%20,%21,%22,%23,%24,%25,%26,%27,%28,%29,%30,%31,%32,%33,%34,%35,%36,%37,%38,%39,%40,%41,%42,%43,%44,%45,%46,%47},{%48,%49,%50,%51},%52,p,1,1,0;\n}\n"
  : "+f"(c[0]),"+f"(c[1]),"+f"(c[2]),"+f"(c[3]),"+f"(c[4]),"+f"(c[5]),"+f"(c[6]),"+f"(c[7]),"+f"(c[8]),"+f"(c[9]),"+f"(c[10]),"+f"(c[11]),"+f"(c[12]),"+f"(c[13]),"+f"(c[14]),"+f"(c[15]),"+f"(c[16]),"+f"(c[17]),"+f"(c[18]),"+f"(c[19]),"+f"(c[20]),"+f"(c[21]),"+f"(c[22]),"+f"(c[23]),"+f"(c[24]),"+f"(c[25]),"+f"(c[26]),"+f"(c[27]),"+f"(c[28]),"+f"(c[29]),"+f"(c[30]),"+f"(c[31]),"+f"(c[32]),"+f"(c[33]),"+f"(c[34]),"+f"(c[35]),"+f"(c[36]),"+f"(c[37]),"+f"(c[38]),"+f"(c[39]),"+f"(c[40]),"+f"(c[41]),"+f"(c[42]),"+f"(c[43]),"+f"(c[44]),"+f"(c[45]),"+f"(c[46]),"+f"(c[47])
  : "r"(a[0]),"r"(a[1]),"r"(a[2]),"r"(a[3]),"l"(db),"r"(sd));
}
};
template<> struct RS<112>{ static __device__ __forceinline__ void run(float (&c)[64], const uint32_t* a, uint64_t db, int sd){
 asm volatile("{\n.reg .pred p;\nsetp.ne.b32 p, %61, 0;\nwgmma.mma_async.sync.aligned.m64n112k16.f32.bf16.bf16 {%0,%1,%2,%3,%4,%5,%6,%7,%8,%9,%10,%11,%12,%13,%14,%15,%16,%17,%18,%19,%20,%21,%22,%23,%24,%25,%26,%27,%28,%29,%30,%31,%32,%33,%34,%35,%36,%37,%38,%39,%40,%41,%42,%43,%44,%45,%46,%47,%48,%49,%50,%51,%52,%53,%54,%55},{%56,%57,%58,%59},%60,p,1,1,0;\n}\n"
  : "+f"(c[0]),"+f"(c[1]),"+f"(c[2]),"+f"(c[3]),"+f"(c[4]),"+f"(c[5]),"+f"(c[6]),"+f"(c[7]),"+f"(c[8]),"+f"(c[9]),"+f"(c[10]),"+f"(c[11]),"+f"(c[12]),"+f"(c[13]),"+f"(c[14]),"+f"(c[15]),"+f"(c[16]),"+f"(c[17]),"+f"(c[18]),"+f"(c[19]),"+f"(c[20]),"+f"(c[21]),"+f"(c[22]),"+f"(c[23]),"+f"(c[24]),"+f"(c[25]),"+f"(c[26]),"+f"(c[27]),"+f"(c[28]),"+f"(c[29]),"+f"(c[30]),"+f"(c[31]),"+f"(c[32]),"+f"(c[33]),"+f"(c[34]),"+f"(c[35]),"+f"(c[36]),"+f"(c[37]),"+f"(c[38]),"+f"(c[39]),"+f"(c[40]),"+f"(c[41]),"+f"(c[42]),"+f"(c[43]),"+f"(c[44]),"+f"(c[45]),"+f"(c[46]),"+f"(c[47]),"+f"(c[48]),"+f"(c[49]),"+f"(c[50]),"+f"(c[51]),"+f"(c[52]),"+f"(c[53]),"+f"(c[54]),"+f"(c[55])
  : "r"(a[0]),"r"(a[1]),"r"(a[2]),"r"(a[3]),"l"(db),"r"(sd));
}
};
template<> struct RS<128>{ static __device__ __forceinline__ void run(float (&c)[64], const uint32_t* a, uint64_t db, int sd){
 asm volatile("{\n.reg .pred p;\nsetp.ne.b32 p, %69, 0;\nwgmma.mma_async.sync.aligned.m64n128k16.f32.bf16.bf16 {%0,%1,%2,%3,%4,%5,%6,%7,%8,%9,%10,%11,%12,%13,%14,%15,%16,%17,%18,%19,%20,%21,%22,%23,%24,%25,%26,%27,%28,%29,%30,%31,%32,%33,%34,%35,%36,%37,%38,%39,%40,%41,%42,%43,%44,%45,%46,%47,%48,%49,%50,%51,%52,%53,%54,%55,%56,%57,%58,%59,%60,%61,%62,%63},{%64,%65,%66,%67},%68,p,1,1,0;\n}\n"
  : "+f"(c[0]),"+f"(c[1]),"+f"(c[2]),"+f"(c[3]),"+f"(c[4]),"+f"(c[5]),"+f"(c[6]),"+f"(c[7]),"+f"(c[8]),"+f"(c[9]),"+f"(c[10]),"+f"(c[11]),"+f"(c[12]),"+f"(c[13]),"+f"(c[14]),"+f"(c[15]),"+f"(c[16]),"+f"(c[17]),"+f"(c[18]),"+f"(c[19]),"+f"(c[20]),"+f"(c[21]),"+f"(c[22]),"+f"(c[23]),"+f"(c[24]),"+f"(c[25]),"+f"(c[26]),"+f"(c[27]),"+f"(c[28]),"+f"(c[29]),"+f"(c[30]),"+f"(c[31]),"+f"(c[32]),"+f"(c[33]),"+f"(c[34]),"+f"(c[35]),"+f"(c[36]),"+f"(c[37]),"+f"(c[38]),"+f"(c[39]),"+f"(c[40]),"+f"(c[41]),"+f"(c[42]),"+f"(c[43]),"+f"(c[44]),"+f"(c[45]),"+f"(c[46]),"+f"(c[47]),"+f"(c[48]),"+f"(c[49]),"+f"(c[50]),"+f"(c[51]),"+f"(c[52]),"+f"(c[53]),"+f"(c[54]),"+f"(c[55]),"+f"(c[56]),"+f"(c[57]),"+f"(c[58]),"+f"(c[59]),"+f"(c[60]),"+f"(c[61]),"+f"(c[62]),"+f"(c[63])
  : "r"(a[0]),"r"(a[1]),"r"(a[2]),"r"(a[3]),"l"(db),"r"(sd));
}
 static __device__ __forceinline__ void first(float (&c)[64], const uint32_t* a, uint64_t db){
 asm volatile("{\n.reg .pred p;\nsetp.ne.b32 p, 0, 0;\nwgmma.mma_async.sync.aligned.m64n128k16.f32.bf16.bf16 {%0,%1,%2,%3,%4,%5,%6,%7,%8,%9,%10,%11,%12,%13,%14,%15,%16,%17,%18,%19,%20,%21,%22,%23,%24,%25,%26,%27,%28,%29,%30,%31,%32,%33,%34,%35,%36,%37,%38,%39,%40,%41,%42,%43,%44,%45,%46,%47,%48,%49,%50,%51,%52,%53,%54,%55,%56,%57,%58,%59,%60,%61,%62,%63},{%64,%65,%66,%67},%68,p,1,1,0;\n}\n"
  : "=f"(c[0]),"=f"(c[1]),"=f"(c[2]),"=f"(c[3]),"=f"(c[4]),"=f"(c[5]),"=f"(c[6]),"=f"(c[7]),"=f"(c[8]),"=f"(c[9]),"=f"(c[10]),"=f"(c[11]),"=f"(c[12]),"=f"(c[13]),"=f"(c[14]),"=f"(c[15]),"=f"(c[16]),"=f"(c[17]),"=f"(c[18]),"=f"(c[19]),"=f"(c[20]),"=f"(c[21]),"=f"(c[22]),"=f"(c[23]),"=f"(c[24]),"=f"(c[25]),"=f"(c[26]),"=f"(c[27]),"=f"(c[28]),"=f"(c[29]),"=f"(c[30]),"=f"(c[31]),"=f"(c[32]),"=f"(c[33]),"=f"(c[34]),"=f"(c[35]),"=f"(c[36]),"=f"(c[37]),"=f"(c[38]),"=f"(c[39]),"=f"(c[40]),"=f"(c[41]),"=f"(c[42]),"=f"(c[43]),"=f"(c[44]),"=f"(c[45]),"=f"(c[46]),"=f"(c[47]),"=f"(c[48]),"=f"(c[49]),"=f"(c[50]),"=f"(c[51]),"=f"(c[52]),"=f"(c[53]),"=f"(c[54]),"=f"(c[55]),"=f"(c[56]),"=f"(c[57]),"=f"(c[58]),"=f"(c[59]),"=f"(c[60]),"=f"(c[61]),"=f"(c[62]),"=f"(c[63])
  : "r"(a[0]),"r"(a[1]),"r"(a[2]),"r"(a[3]),"l"(db));
}
};

struct Maps { const CUtensorMap *k, *v, *q, *ob; };
__device__ __forceinline__ void p0_issue(const Maps& m, uint32_t kb, uint32_t vlast, uint32_t bar, int col0, int row0) {
  mbar_expect_tx(bar, LSET_TX);
#pragma unroll
  for (int i = 0; i < 4; i++) {
    tma3d(kb + i * LKP, m.k, col0, (row0 >> 3) - 1, 2 * i, bar);
    tma3d(i < 3 ? kb + LV_OFF + i * LVP : vlast, m.v, col0, row0 >> 3, 2 * i, bar);
  }
}
template <int CL>
__device__ __forceinline__ void p0_task(const Params& p, uint32_t sb, uint32_t ubase, uint32_t kb, uint32_t vlast, uint32_t bar, uint32_t par,
                                        int toct, int olo, int nb, int row0, int task, uint32_t en) {
  constexpr int CPC = 8 / CL;
  const int rg = task / nb, ol = task - rg * nb;
  if (CL == 8 && task == 0) PSTAMP(en ? 34 : 37);
  uint32_t w[16];
  {
    const int oct = toct + olo + ol;
#pragma unroll
    for (int c = 0; c < 4; c++) {
      uint4 sk = ldg128c(p.shift_k + oct * 32 + c * 8);
      w[4 * c] = prmt(sk.x, sk.z, 0x5410); w[4 * c + 1] = prmt(sk.x, sk.z, 0x7632);
      w[4 * c + 2] = prmt(sk.y, sk.w, 0x5410); w[4 * c + 3] = prmt(sk.y, sk.w, 0x7632);
    }
  }
  const uint32_t lo = rg * 80 + (olo + ol) * 16;
  const uint32_t ka = kb + lo, va = ka + LV_OFF, vl = vlast + lo;
  if (CL == 8 && task == 0) PSTAMP(en ? 30 : 38);
  mbar_wait(bar, par);
  if (CL == 8 && task == 0) PSTAMP(en ? 31 : 39);
  if (CL == 8 && task == 128) PSTAMP(33);
  uint4 kr[11], vr[8];
#pragma unroll
  for (int i = 0; i < 11; i++) {
    const int pl = (i + 5) & 7;
    kr[i] = lds128(ka + (pl >> 1) * LKP + (pl & 1) * (LKB / 2) + (i < 3 ? 0 : 80));
  }
#pragma unroll
  for (int i = 0; i < 8; i++) vr[i] = lds128(i < 6 ? va + i * (LVP / 2) : vl + (i - 6) * (LVP / 2));
  if (CL == 8 && task == 0) PSTAMP(en ? 35 : 40);
  uint32_t x[8][4];
#pragma unroll
  for (int i = 0; i < 8; i++) {
    const uint32_t* k0 = (const uint32_t*)&kr[i];
    const uint32_t* k1 = (const uint32_t*)&kr[i + 1];
    const uint32_t* k2 = (const uint32_t*)&kr[i + 2];
    const uint32_t* k3 = (const uint32_t*)&kr[i + 3];
    const uint32_t* vv = (const uint32_t*)&vr[i];
#pragma unroll
    for (int c = 0; c < 4; c++) {
      uint32_t s = badd(bmul(k0[c], w[4 * c + 3]), bmul(k1[c], w[4 * c + 2]));
      s = badd(s, bmul(k2[c], w[4 * c + 1]));
      s = badd(s, bmul(k3[c], w[4 * c]));
      x[i][c] = bmul(s, vv[c]);
    }
  }
  if (CL == 8 && task == 0) PSTAMP(en ? 32 : 41);
  uint32_t off = (uint32_t)(2040 - row0 - rg * 8) * 2;
  off ^= ((off >> 7) & 1) << 4;
#pragma unroll
  for (int ch = 0; ch < 8; ch++) {
    const int c = ch >> 1;
    const uint32_t sel = (ch & 1) ? 0x7632 : 0x5410;
    uint32_t y0 = prmt(x[7][c], x[6][c], sel), y1 = prmt(x[5][c], x[4][c], sel);
    uint32_t y2 = prmt(x[3][c], x[2][c], sel), y3 = prmt(x[1][c], x[0][c], sel);
    const int slot = ol * CPC + (ch % CPC);
    uint32_t ra = mapa(ubase + slot * USLOT + off, ch / CPC);
    uint32_t rb = mapa(sb + OFF_BAR + (B_UFULL + slot) * 8, ch / CPC);
    asm volatile("{\n.reg .pred p;\nsetp.ne.u32 p, %6, 0;\n@p st.async.weak.shared::cluster.mbarrier::complete_tx::bytes.v4.b32 [%0], {%1,%2,%3,%4}, [%5];\n}\n" ::"r"(ra), "r"(y0), "r"(y1), "r"(y2), "r"(y3), "r"(rb), "r"(en) : "memory");
  }
}

template <int CL>
__device__ __forceinline__ uint32_t ost_addr(uint32_t sb, int task) {
  if (CL == 8) return sb + OFF_OST + (task & 1) * 4096;
  return sb + OFF_OST2 + task * 4096;
}

template <int CL>
__device__ __forceinline__ void conv_out(const Maps& mp, uint32_t sb, uint32_t qbuf, uint32_t qbar, uint32_t qpar, int oct, int task, int seg,
                                         int next_oct, int lane) {
  const int rho = (lane >> 4) * 8 + ((lane & 15) >> 1);
  const uint32_t roff = (uint32_t)(255 - (64 * (lane & 1) + rho)) * 16;
  const uint32_t buf = ost_addr<CL>(sb, task);
  mbar_wait(sb + OFF_BAR + ((CL == 8 ? B_OFULL8 : B_OFULL2) + task) * 8, 0);
  uint4 y[8];
#pragma unroll
  for (int ch = 0; ch < 8; ch++) y[ch] = lds128(buf + lane * 16 + ch * 512);
  mbar_wait(qbar, qpar);
  uint4 o[8];
#pragma unroll
  for (int m = 0; m < 8; m++) {
    const int wd = m >> 1;
    const int b = (wd & 1) * 8 + (wd >> 1) * 2 + (m & 1);
    const uint4 qv = lds128(qbuf + roff - b * 256);
    const uint32_t sel = (m & 1) ? 0x7632 : 0x5410;
    uint32_t* oo = (uint32_t*)&o[m];
#pragma unroll
    for (int c = 0; c < 4; c++) {
      const uint32_t* ya = (const uint32_t*)&y[2 * c];
      const uint32_t* yb = (const uint32_t*)&y[2 * c + 1];
      oo[c] = bmul(((const uint32_t*)&qv)[c], prmt(ya[wd], yb[wd], sel));
      asm volatile("" : "+r"(oo[c])::"memory");
    }
  }
  __syncwarp();
#pragma unroll
  for (int m = 0; m < 8; m++) {
    const int wd = m >> 1;
    const int b = (wd & 1) * 8 + (wd >> 1) * 2 + (m & 1);
    sts128(buf + roff - b * 256, o[m].x, o[m].y, o[m].z, o[m].w);
  }
  fence_async();
  __syncwarp();
  if (lane == 0) {
    tma_store2d(mp.ob, buf, 640 + oct * 8, seg * 256);
    bulk_commit();
    if (next_oct >= 0) { mbar_expect_tx(qbar, 4096); tma2d(qbuf, mp.q, next_oct * 8, seg * 256, qbar); }
    bulk_wait_read();
  }
  __syncwarp();
  if (CL == 8 && task < 3 && lane < 8) mbar_arrive_rem(mapa(sb + OFF_BAR + (B_OFREE + task) * 8, lane));
}

__device__ __forceinline__ void load_a(uint32_t (&a)[16], uint32_t ka) {
#pragma unroll
  for (int i = 0; i < 4; i++) {
    a[4 * i] = lds32(ka + 128 * i);
    a[4 * i + 1] = lds32(ka + 128 * i - 32);
    a[4 * i + 2] = lds32(ka + 128 * i + 16);
    a[4 * i + 3] = lds32(ka + 128 * i - 16);
  }
}

struct ConvCtx {
  uint32_t sb, xw, xr, lane, q, w1;
  uint32_t ulane;
  uint32_t olane;
  int barid;
  float pT0, pT1;
};

struct Ret { float T0, T1, T2, T3; uint32_t u0, u1; };
template <int P>
__device__ __forceinline__ void retire1(ConvCtx& x, Ret& t, const float* v, float nx, uint32_t uslot) {
  const int srcl = (x.lane & ~3) | ((x.q + 1) & 3);
  float s0 = x.q == 0 ? v[4] : v[0], s1 = x.q == 0 ? nx : v[4];
  float sh0 = __shfl_sync(0xffffffffu, s0, srcl), sh1 = __shfl_sync(0xffffffffu, s1, srcl);
  t.T0 = v[2] + v[1]; t.T1 = v[3] + sh0; t.T2 = v[6] + v[5]; t.T3 = v[7] + sh1;
  float p0 = P == 7 ? 0.f : x.pT0, p1 = P == 7 ? 0.f : x.pT1;
  float o0 = x.q == 0 ? t.T2 : t.T0, o1 = x.q == 0 ? t.T3 : t.T1, o2 = x.q == 0 ? p0 : t.T2, o3 = x.q == 0 ? p1 : t.T3;
  t.u0 = 0; t.u1 = 0;
  asm volatile("{\n.reg .pred p;\nsetp.ne.u32 p, %3, 0;\n@p ldmatrix.sync.aligned.m8n8.x2.trans.shared.b16 {%0,%1}, [%2];\n}\n" : "+r"(t.u0), "+r"(t.u1) : "r"(uslot + P * 512 + x.ulane), "r"(x.w1) : "memory");
  asm volatile("{\n.reg .pred p;\nsetp.eq.u32 p, %5, 0;\n@p st.shared.v4.f32 [%0], {%1,%2,%3,%4};\n}\n" ::"r"(x.xw + (P & 1) * 1024), "f"(o0), "f"(o1), "f"(o2), "f"(o3), "r"(x.w1) : "memory");
  x.pT0 = t.T0; x.pT1 = t.T1;
}
template <int CL, int P>
__device__ __forceinline__ void retire2(ConvCtx& x, const Ret& t, uint32_t D2, int oloc, int chi, uint32_t en) {
  constexpr int SEGS = 8 / CL;
  uint4 r = make_uint4(0, 0, 0, 0);
#if !(XP & 2)
  asm volatile("{\n.reg .pred p;\nsetp.ne.u32 p, %5, 0;\n@p ld.shared.v4.u32 {%0,%1,%2,%3}, [%4];\n}\n" : "+r"(r.x), "+r"(r.y), "+r"(r.z), "+r"(r.w) : "r"(x.xr + (P & 1) * 1024), "r"(x.w1) : "memory");
#endif
  uint32_t y0 = pack_bf16(t.T0 + __uint_as_float(r.x), t.T1 + __uint_as_float(r.y));
  uint32_t y1 = pack_bf16(t.T2 + __uint_as_float(r.z), t.T3 + __uint_as_float(r.w));
  y0 = badd(y0, bmul(t.u0, D2));
  y1 = badd(y1, bmul(t.u1, D2));
  constexpr int owner = (7 - P) / SEGS;
  const int task = oloc * SEGS + (7 - P) % SEGS;
  uint32_t ra = mapa(ost_addr<CL>(x.sb, task) + chi * 512 + x.olane, owner);
  uint32_t rb = mapa(x.sb + OFF_BAR + ((CL == 8 ? B_OFULL8 : B_OFULL2) + task) * 8, owner);
  asm volatile("{\n.reg .pred p;\nsetp.ne.u32 p, %4, 0;\n@p st.async.weak.shared::cluster.mbarrier::complete_tx::bytes.v2.b32 [%0], {%1,%2}, [%3];\n}\n" ::"r"(ra), "r"(y0), "r"(y1), "r"(rb), "r"(en) : "memory");
}

template <int CL>
__device__ __forceinline__ void k_builder(const Params& p, uint32_t kbase, uint32_t kbar, int rank, int oct0, int first, int nch, int lane) {
  constexpr int CPC = 8 / CL, STEP = CL == 8 ? 1 : 3;
  int it = 0;
#pragma unroll 1
  for (int ci = first; ci < nch; ci += STEP, it++) {
    const int ch = (oct0 + ci / CPC) * 8 + rank * CPC + ci % CPC;
    const bf16* src = p.ssm_k + (size_t)ch * 2048 + lane * 8;
    uint4 d[8];
    uint32_t pv[8];
#pragma unroll
    for (int i = 0; i < 8; i++) {
      d[i] = ldg128c(src + i * 256);
      pv[i] = (i > 0 || lane > 0) ? __ldg((const uint32_t*)(src + i * 256 - 2)) : 0u;
    }
    if (it == 0) cluster_wait();
#pragma unroll
    for (int qt = 0; qt < 4; qt++) {
      if (it > 0) mbar_wait(kbar + (4 + qt) * 8, (it - 1) & 1);
#pragma unroll
      for (int h = 0; h < 2; h++) {
        const int i = 2 * qt + h;
        const uint32_t o = kbase + 128 + i * 512 + lane * 16;
        sts128(o + KE_OFF, d[i].x, d[i].y, d[i].z, d[i].w);
        sts128(o, __funnelshift_l(pv[i], d[i].x, 16), __funnelshift_l(d[i].x, d[i].y, 16), __funnelshift_l(d[i].y, d[i].z, 16),
               __funnelshift_l(d[i].z, d[i].w, 16));
      }
      __syncwarp();
      if (lane == 0) mbar_arrive(kbar + qt * 8);
    }
  }
}

template <int CL, int PH>
__device__ __forceinline__ void conv_phase(ConvCtx& x, float (&c)[64], uint32_t (&a)[16], uint32_t (&an)[16], uint64_t d0, uint32_t ka, uint32_t kwait,
                                           uint32_t kpar, uint32_t en, const float* v, float nx, uint32_t uslot, uint32_t D2, int oloc, int chi) {
  constexpr int N = 128 - 16 * PH, P = (8 - PH) & 7;
  if (PH > 0) {
#pragma unroll
    for (int i = 0; i < N / 2; i++) asm volatile("mov.b32 %0, %1;" : "=f"(c[i]) : "f"(c[i]) : "memory");
  }
  Ret t;
  wg_fence();
  if constexpr (PH == 0) RS<128>::first(c, &a[0], d0);
  else RS<N>::run(c, &a[0], d0 + (4 * PH) * 8, 1);
  RS<N>::run(c, &a[4], d0 + (4 * PH + 1) * 8, 1);
  RS<N>::run(c, &a[8], d0 + (4 * PH + 2) * 8, 1);
  RS<N>::run(c, &a[12], d0 + (4 * PH + 3) * 8, 1);
  wg_commit();
#if !(XP & 1)
  load_a(an, ka + ((PH + 1) & 7) * 512);
#endif
#if !(XP & 2)
  retire1<P>(x, t, v, nx, uslot);
#else
  t.T0 = v[0]; t.T1 = v[1]; t.T2 = v[2]; t.T3 = v[3]; t.u0 = 0; t.u1 = 0;
#endif
#if !(XP & 4)
  bar_sync(CL == 8 ? 1 : x.barid, 128);
#endif
  retire2<CL, P>(x, t, D2, oloc, chi, en);
  if (!(PH & 1)) mbar_wait(kwait, kpar);
}

template <int CL>
__device__ __forceinline__ void conv_main(const Params& p, uint32_t sb, uint32_t ubase, uint32_t kbase, uint32_t xbase, uint32_t kbar, int barid,
                                          int rank, int oct0, int first, int nch, int tid) {
  constexpr int CPC = 8 / CL, STEP = CL == 8 ? 1 : 3;
  const int lane = tid & 31, w = tid >> 5, g = lane >> 2, q = lane & 3, w0 = w & 1, w1 = w >> 1;
  ConvCtx x;
  x.sb = sb; x.lane = lane; x.q = q; x.w1 = w1; x.barid = barid;
  x.xw = xbase + w0 * 512 + ((lane & ~3) | ((q + 3) & 3)) * 16;
  x.xr = xbase + w0 * 512 + lane * 16;
  x.ulane = (32 * (lane & 15) + 16 * w0) ^ (((lane >> 2) & 1) << 4);
  x.olane = (w0 * 32 + lane) * 8;
  x.pT0 = x.pT1 = 0.f;
  const int e = 112 + 2 * q - 32 * w1 - 8 * w0 - g;
  const uint32_t ka = (g & 1) ? kbase + (e + 1) * 2 : kbase + KE_OFF + e * 2;
  float c[64];
  float r[9];
#pragma unroll
  for (int i = 0; i < 9; i++) r[i] = 0.f;
  uint32_t a0[16], a1[16];
  uint32_t pslot = ubase, pD2 = 0, par = 0;
  int poloc = 0, pchi = 0;
  mbar_wait(kbar, 0);
  load_a(a0, ka);
  for (int ci = first; ci < nch; ci += STEP) {
    const int oloc = ci / CPC, chi = rank * CPC + ci % CPC;
    const int ch = (oct0 + oloc) * 8 + chi;
    const bool more = ci + STEP < nch;
    const uint32_t uslot = ubase + ci * USLOT;
    uint32_t D2 = *(const unsigned short*)(p.ssm_D + ch);
    D2 |= D2 << 16;
    const uint64_t d0 = make_desc(uslot, 16, 256, 3);
    if (tid == 0) PSTAMP(12 + 2 * ci);
    mbar_wait(sb + OFF_BAR + (B_UFULL + ci) * 8, 0);
    fence_async();
    if (tid == 0) PSTAMP(13 + 2 * ci);
    conv_phase<CL, 0>(x, c, a0, a1, d0, ka, kbar + 8, par, ci > first ? x.w1 : 0, r, r[8], pslot, pD2, poloc, pchi);
    if (CL == 8 && ci >= 2) mbar_wait(sb + OFF_BAR + (B_OFREE + ci - 2) * 8, 0);
    wg_wait<0>();
    if (CL == 2 && tid == 0 && ci == 2) PSTAMP(36 + 1);
    conv_phase<CL, 1>(x, c, a1, a0, d0, ka, kbar + 8, par, x.w1, &c[56], 0.f, uslot, D2, oloc, chi);
    wg_wait<0>();
    if (CL == 2 && tid == 0 && ci == 2) PSTAMP(36 + 2);
    conv_phase<CL, 2>(x, c, a0, a1, d0, ka, kbar + 16, par, x.w1, &c[48], c[56], uslot, D2, oloc, chi);
    if (more && tid == 0) mbar_arrive(kbar + 32);
    wg_wait<0>();
    if (CL == 2 && tid == 0 && ci == 2) PSTAMP(36 + 3);
    conv_phase<CL, 3>(x, c, a1, a0, d0, ka, kbar + 16, par, x.w1, &c[40], c[48], uslot, D2, oloc, chi);
    wg_wait<0>();
    if (CL == 2 && tid == 0 && ci == 2) PSTAMP(36 + 4);
    conv_phase<CL, 4>(x, c, a0, a1, d0, ka, kbar + 24, par, x.w1, &c[32], c[40], uslot, D2, oloc, chi);
    if (more && tid == 0) mbar_arrive(kbar + 40);
    wg_wait<0>();
    if (CL == 2 && tid == 0 && ci == 2) PSTAMP(36 + 5);
    conv_phase<CL, 5>(x, c, a1, a0, d0, ka, kbar + 24, par, x.w1, &c[24], c[32], uslot, D2, oloc, chi);
    wg_wait<0>();
    if (CL == 2 && tid == 0 && ci == 2) PSTAMP(36 + 6);
    conv_phase<CL, 6>(x, c, a0, a1, d0, ka, kbar, more ? par ^ 1 : par, x.w1, &c[16], c[24], uslot, D2, oloc, chi);
    if (more && tid == 0) mbar_arrive(kbar + 48);
    wg_wait<0>();
    if (CL == 2 && tid == 0 && ci == 2) PSTAMP(36 + 7);
    conv_phase<CL, 7>(x, c, a1, a0, d0, ka, kbar, more ? par ^ 1 : par, x.w1, &c[8], c[16], uslot, D2, oloc, chi);
    if (more && tid == 0) mbar_arrive(kbar + 56);
    wg_wait<0>();
#pragma unroll
    for (int i = 0; i < 9; i++) asm volatile("mov.b32 %0, %1;" : "=f"(r[i]) : "f"(c[i]) : "memory");
    pslot = uslot; pD2 = D2; poloc = oloc; pchi = chi; par ^= 1;
  }
  {
    Ret t;
    retire1<0>(x, t, r, r[8], pslot);
    bar_sync(CL == 8 ? 1 : x.barid, 128);
    retire2<CL, 0>(x, t, pD2, poloc, pchi, x.w1);
  }
}

__device__ __forceinline__ uint32_t pslot_off(int r, int src) { return (r == 2 ? OFF_W : (r == 1 || r == 4) ? 32768 : 0) + src * 8192; }

template <int CL>
__device__ __forceinline__ void gemm_consumer(const CUtensorMap* mOa, uint32_t sb, int wg, int tid, int rank, int half, int j, int tt) {
  const int lane = tid & 31, w = tid >> 5;
  const uint32_t bars = sb + OFF_BAR;
  constexpr int NREL = CL == 8 ? 5 : 2, NPF = CL == 8 ? 3 : 1;
  uint32_t rel = 0;
  if (tid < NREL) {
    int tgt = CL == 8 ? (tid < 4 ? half * 4 + tid : rank ^ 4) : tid;
    rel = mapa(bars + B_EMPTY * 8, tgt);
  }
  asm volatile("setmaxnreg.inc.sync.aligned.u32 152;");
  float acc[80];
#pragma unroll
  for (int i = 0; i < 80; i++) acc[i] = 0.f;
  int s = 0, sp = 0;
  uint32_t ph = 0;
#pragma unroll 1
  for (int k = 0; k < 32; k++) {
    mbar_wait(bars + (B_FULL + s) * 8, ph);
    if (tid == 0 && wg == 0 && (k & 3) == 0) PSTAMP(44 + (k >> 2));
    const uint32_t st = sb + (s == 0 ? 4 : s - 1) * STG_BYTES;
    const uint64_t da = make_desc(st + wg * 8192, 16, 1024, 1), db = make_desc(st + A_BYTES, 2048, 512, 2);
#pragma unroll
    for (int kk = 0; kk < 4; kk++) {
      wg_fence();
      ss160<1, 0>(acc, da + kk * 2, db + (kk >> 1) * (B_BYTES / 32) + (kk & 1) * 64, 1);
      wg_commit();
      wg_wait<1>();
      if (kk == 0 && k > 0 && k <= 30 && tid < NREL) mbar_arrive_rem(rel + sp * 8);
    }
    sp = s;
    if (++s == NSTG || k == 3) { s = 0; ph ^= 1; }
  }
  wg_wait<0>();
#pragma unroll
  for (int i = 0; i < 80; i++) asm volatile("" : "+f"(acc[i])::"memory");
  if (tid == 0 && wg == 0) PSTAMP(2);
  const uint32_t pfr = mapa(bars + B_PFREE * 8, CL == 8 ? half * 4 + ((j + 1 + tid) & 3) : rank);
  if (tid < NPF) mbar_arrive_rem(pfr);
  if (tid == 32) mbar_arrive(bars + B_DRAIN * 8);
  uint32_t pk[40];
#pragma unroll
  for (int i = 0; i < 40; i++) { pk[i] = pack_bf16(acc[2 * i], acc[2 * i + 1]); asm volatile("" : "+r"(pk[i])::"memory"); }
  const uint64_t dw0 = make_desc(sb + OFF_W, 16, 512, 2);
  const int row = 16 * w + (lane & 7) + 8 * ((lane >> 3) & 1);
  const uint32_t sa0 = sb + wg * 4096 + row * 64 + (((lane >> 4) ^ ((row >> 1) & 3)) << 4), sa1 = sa0 ^ 32;
  mbar_wait(bars + B_EMPTY * 8, 0);
  stsm4(sa0 + OFF_SPY, pk[0], pk[1], pk[2], pk[3]);
  stsm4(sa1 + OFF_SPY, pk[4], pk[5], pk[6], pk[7]);
  fence_async();
  __syncwarp();
  if (lane == 0) mbar_arrive(bars + B_STAGED * 8);
  mbar_wait(bars + B_WFULL * 8, 0);
  wg_fence();
  RS<160>::first(acc, &pk[0], dw0);
  RS<160>::run(acc, &pk[4], dw0 + 2, 1);
  wg_commit();
  mbar_wait(bars + B_DRAIN * 8, 0);
  stsm4(sa0 + j * 8192, pk[8], pk[9], pk[10], pk[11]);
  stsm4(sa1 + j * 8192, pk[12], pk[13], pk[14], pk[15]);
  stsm4(sa0 + j * 8192 + 32768, pk[16], pk[17], pk[18], pk[19]);
  stsm4(sa1 + j * 8192 + 32768, pk[20], pk[21], pk[22], pk[23]);
  stsm4(sa0 + OFF_SPX, pk[24], pk[25], pk[26], pk[27]);
  stsm4(sa1 + OFF_SPX, pk[28], pk[29], pk[30], pk[31]);
  fence_async();
  __syncwarp();
  if (lane == 0) mbar_arrive(bars + (B_STAGED + 1) * 8);
#pragma unroll
  for (int c = 1; c < 5; c++) {
    mbar_wait(bars + (B_WFULL + c) * 8, 0);
    wg_fence();
    RS<160>::run(acc, &pk[8 * c], dw0 + c * (W_BYTES / 16), 1);
    RS<160>::run(acc, &pk[8 * c + 4], dw0 + c * (W_BYTES / 16) + 2, 1);
    wg_commit();
    wg_wait<1>();
  }
  if (tid < NPF) mbar_arrive_rem(pfr + 8);
  mbar_wait(bars + B_C0FREE * 8, 0);
  stsm4(sa0 + OFF_SPY, pk[32], pk[33], pk[34], pk[35]);
  stsm4(sa1 + OFF_SPY, pk[36], pk[37], pk[38], pk[39]);
  fence_async();
  __syncwarp();
  if (lane == 0) mbar_arrive(bars + (B_STAGED + 2) * 8);
  int ws = 5, wsp = 4;
  uint32_t wph = 0;
#pragma unroll 1
  for (int r = 0; r < 5; r++) {
    if (tid == 0 && wg == 0 && (r & 1) == 0) PSTAMP(3 + (r >> 1));
#pragma unroll 1
    for (int ps = 0; ps < 3; ps++) {
      const int src = (j + 1 + ps) & 3;
      const uint64_t dp = make_desc(sb + pslot_off(r, src) + wg * 4096, 16, 512, 2);
      mbar_wait(bars + (B_PFULL + r * 4 + src) * 8, 0);
      if (tid == 0 && wg == 0 && r < 2 && ps != 1) PSTAMP(22 + r * 2 + (ps >> 1));
      mbar_wait(bars + (B_WFULL + ws) * 8, wph);
      const uint64_t dw = dw0 + ws * (W_BYTES / 16);
      wg_fence();
      ss160<0, 0>(acc, dp, dw, 1);
      wg_commit();
      wg_wait<1>();
      if (r * 3 + ps <= 9 && tid == 32) mbar_arrive(bars + (B_WEMPTY + wsp - 4) * 8);
      if (ps == 0) {
        if ((r == 1 || r == 2) && tid < NPF) mbar_arrive_rem(pfr + 8 + r * 8);
        if (r == 3 && tid == 0) mbar_arrive_rem(mapa(bars + B_XFREE * 8, rank ^ (CL / 2)));
      }
      wg_fence();
      ss160<0, 0>(acc, dp + 2, dw + 2, 1);
      wg_commit();
      wg_wait<1>();
      wsp = ws;
      if (++ws == 10) { ws = 4; wph ^= 1; }
    }
  }
  wg_wait<0>();
#pragma unroll
  for (int i = 0; i < 80; i++) asm volatile("" : "+f"(acc[i])::"memory");
  if (tid == 0 && wg == 0) PSTAMP(6);
  mbar_wait(bars + B_XFREE * 8, 0);
  {
    const uint32_t xw = sb + OFF_XCH + wg * 10240 + w * 2560;
    const uint32_t xl = xw + lane * 16;
    const uint32_t xr = mapa(xl, rank ^ (CL / 2));
    const uint32_t xb = mapa(bars + (B_XFULL + wg) * 8, rank ^ (CL / 2));
#pragma unroll
    for (int i = 0; i < 5; i++) {
      uint32_t sv[4];
#pragma unroll
      for (int m = 0; m < 4; m++) {
        const int idx = 8 * i + 2 * m;
        float lo = half ? acc[idx] : acc[40 + idx], hi = half ? acc[idx + 1] : acc[41 + idx];
        sv[m] = pack_bf16(lo, hi);
      }
      st_async4(xr + i * 512, sv[0], sv[1], sv[2], sv[3], xb);
    }
    mbar_wait(bars + (B_XFULL + wg) * 8, 0);
    const float sg = half ? -1.f : 1.f;
    const uint32_t oa = xw + ((lane & 7) + 8 * ((lane >> 3) & 1)) * 160 + (lane >> 4) * 16;
    uint32_t ov[20];
#pragma unroll
    for (int i = 0; i < 5; i++) {
      uint4 rv = lds128(xl + i * 512);
      const uint32_t* rr = (const uint32_t*)&rv;
#pragma unroll
      for (int m = 0; m < 4; m++) {
        const int idx = 8 * i + 2 * m;
        float lo = half ? acc[40 + idx] : acc[idx], hi = half ? acc[41 + idx] : acc[idx + 1];
        float rl = __uint_as_float(rr[m] << 16), rh = __uint_as_float(rr[m] & 0xffff0000u);
        ov[4 * i + m] = pack_bf16(sg * (lo - rl), sg * (hi - rh));
        asm volatile("" : "+r"(ov[4 * i + m])::"memory");
      }
    }
    __syncwarp();
#pragma unroll
    for (int i = 0; i < 5; i++) stsm4(oa + i * 32, ov[4 * i], ov[4 * i + 1], ov[4 * i + 2], ov[4 * i + 3]);
    fence_async();
    __syncwarp();
    if (lane == 0) {
      tma_store2d(mOa, xw, j * 160 + half * 80, tt * 128 + wg * 64 + w * 16);
      bulk_commit();
      bulk_wait_read();
    }
  }
  if (tid == 0 && wg == 0) { PSTAMP(7); PGT(63); }
}

template <int CL>
__global__ void __launch_bounds__(512, 1)
fused_kernel(const __grid_constant__ CUtensorMap mCr, const __grid_constant__ CUtensorMap mCi, const __grid_constant__ CUtensorMap mX,
             const __grid_constant__ CUtensorMap mWr, const __grid_constant__ CUtensorMap mWi, const __grid_constant__ CUtensorMap mKin,
             const __grid_constant__ CUtensorMap mVin, const __grid_constant__ CUtensorMap mQ, const __grid_constant__ CUtensorMap mOa,
             const __grid_constant__ CUtensorMap mOb,
             const __grid_constant__ Params p) {
  extern __shared__ __align__(1024) unsigned char smem[];
  const uint32_t sb = smem_u32(smem);
  const uint32_t bars = sb + OFF_BAR;
  const int wg = __shfl_sync(0xffffffffu, threadIdx.x >> 7, 0);
  const int tid = threadIdx.x & 127, lane = threadIdx.x & 31;
  const int warp = __shfl_sync(0xffffffffu, tid >> 5, 0);
  const uint32_t ctouch = ((const uint32_t*)&mCr)[tid < 32 ? -42 : tid < 64 ? -14 : 320];
  uint32_t rank;
  asm("mov.u32 %0, %%cluster_ctarank;" : "=r"(rank));
  const int cid = blockIdx.x / CL;
  constexpr int SEGS = 8 / CL;
  bool gemm;
  int tt, half, j, oct0, noct;
  if (CL == 8) {
    asm volatile("griddepcontrol.launch_dependents;");
    gemm = true; tt = cid; half = rank >> 2; j = rank & 3; oct0 = 5 * cid; noct = 5;
  } else {
    const int ti = cid / 6, c6 = cid % 6;
    tt = p.nA + ti; half = rank; j = c6 & 3; gemm = c6 < 4;
    oct0 = 5 * tt + (c6 == 5 ? 3 : 0);
    noct = gemm ? 0 : (c6 == 4 ? 3 : 2);
  }
  const uint32_t ubase = CL == 8 ? sb + OFF_U : sb;
  if (threadIdx.x == 0) { PSTAMP(0); PGT(62); PZERO(1, 7); PZERO(44, 51); }
  if (threadIdx.x == 256) { PZERO(8, 9); PZERO(12, 43); }
  if (threadIdx.x == 384) PZERO(52, 61);

  {
    const int gw = (wg * 4 + warp + 4) & 15;
    const uint64_t cntt = CL == 8 ? 0x11111111111862A1ull : 0x1111111111182241ull;
    const uint64_t numt = CL == 8 ? 0x0050087858864858ull : (gemm ? 0x0000002848834858ull : 0x8888880004800802ull);
    const uint32_t cnt = (uint32_t)(cntt >> (4 * gw)) & 15, num = (uint32_t)(numt >> (4 * gw)) & 15;
    if (lane == 0) {
#pragma unroll
      for (int i = 0; i < 8; i++)
        if (i < num) mbar_init(bars + gw * 64 + i * 8, cnt);
      asm volatile("fence.mbarrier_init.release.cluster;" ::: "memory");
    }
    __syncwarp();
    if (lane < num) {
      const int i = gw * 8 + lane;
      uint32_t tx = 0;
      if (i >= B_UFULL || (i >= B_OFULL8 && i < B_KBAR)) tx = 4096;
      if (gemm && i >= B_PFULL && i < B_QFULL8) tx = 8192;
      if (i == B_XFULL || i == B_XFULL + 1) tx = 10240;
      if (tx) mbar_expect_tx(bars + i * 8, tx);
      if (!(CL == 8 && noct > 0)) {
        if (i == B_FULL + 4) mbar_arrive(bars + i * 8);
        if (i == B_EMPTY + 4) mbar_arrive_n(bars + i * 8, cnt);
      }
    }
    __syncwarp();
  }
  if (threadIdx.x == 384) PSTAMP(52);
  cluster_arrive();
  if (threadIdx.x == 384) PSTAMP(54);

  Maps mp;
  mp.k = &mKin; mp.v = &mVin; mp.q = &mQ; mp.ob = &mOb;
  const int toct = 5 * tt, olo = oct0 - toct;
  if (wg < 3) {
    if (gemm && wg < 2) {
      asm volatile("{\n.reg .pred p;\nsetp.eq.u32 p, %0, 0x9e3779b9;\n@p st.shared.u32 [%1], %0;\n}\n" ::"r"(ctouch), "r"(bars + 1016) : "memory");
      if (threadIdx.x == 0) PSTAMP(11);
      cluster_wait();
      if (threadIdx.x == 0) PSTAMP(1);
      gemm_consumer<CL>(&mOa, sb, wg, tid, rank, half, j, tt);
      if (threadIdx.x == 0) { PDUMP(0, 7); PDUMP(11, 11); PDUMP(22, 25); PDUMP(44, 51); PDUMP(62, 63); }
    } else if (noct > 0) {
      const uint32_t kbase = CL == 8 ? sb + OFF_K : sb + OFF_K2 + wg * KBUF;
      const uint32_t xbase = CL == 8 ? sb + OFF_X : sb + OFF_X2 + wg * 2048;
      const int first = CL == 8 ? 0 : wg, nch = noct * SEGS, barid = CL == 8 ? 1 : 1 + wg;
      for (int i = first + (CL == 8 ? warp : 3 * warp); i < nch; i += (CL == 8 ? 4 : 12)) sts128(ubase + i * USLOT + 4096 + lane * 16, 0, 0, 0, 0);
      if (tid < 16) sts128(kbase + (tid >> 3) * KE_OFF + (tid & 7) * 16, 0, 0, 0, 0);
      fence_async();
      if (CL == 8 && tid == 0) PSTAMP(28);
      cluster_wait();
      if (CL == 8 && tid == 0) PSTAMP(29);
      if (CL == 8) {
#pragma unroll 1
        for (int t = tid - 128; t < 160; t += 128)
          p0_task<CL>(p, sb, ubase, sb + OFF_LA, sb + OFF_OST, bars + (t < 0 ? B_C0FREE : B_FULL + 4) * 8, t < 0, toct, 0, 5, rank * 256, t < 0 ? tid : t, t >= 0);
        bar_sync(1, 128);
        if (tid < 10) {
          const int t5 = tid < 5 ? tid : tid - 5;
          mbar_arrive_rem(mapa(bars + (B_EMPTY + 4) * 8, t5 < 4 ? half * 4 + t5 : rank ^ 4));
        }
      } else {
        if (wg < 2) {
          const uint32_t lb = sb + OFF_L2 + wg * LSET, lbar = bars + (B_LFULL + wg) * 8;
          if (tid == 0) p0_issue(mp, lb, lb + LV_OFF + 3 * LVP, lbar, toct * 8, rank * 1024 + wg * 256);
#pragma unroll 1
          for (int s2 = 0; s2 < 2; s2++) {
            if (tid < 32 * noct) p0_task<CL>(p, sb, ubase, lb, lb + LV_OFF + 3 * LVP, lbar, s2, toct, olo, noct, rank * 1024 + s2 * 512 + wg * 256, tid, 1);
            bar_sync(barid, 128);
            if (tid == 0 && s2 == 0) p0_issue(mp, lb, lb + LV_OFF + 3 * LVP, lbar, toct * 8, rank * 1024 + 512 + wg * 256);
          }
          if (tid == 0) mbar_arrive(bars + B_DRAIN * 8);
        } else {
          bar_sync(barid, 128);
        }
      }
      if (threadIdx.x == 256) PSTAMP(8);
      asm volatile("setmaxnreg.inc.sync.aligned.u32 136;");
      conv_main<CL>(p, sb, ubase, kbase, xbase, bars + (B_KBAR + (CL == 8 ? 0 : wg * 8)) * 8, barid, rank, oct0, first, nch, tid);
      if (CL == 2 && wg == 2) {
        const int t = nch - 4 + warp;
        conv_out<CL>(mp, sb, sb + OFF_L2 + t * 4096, bars + (B_QFULL2 + t) * 8, 0, oct0 + noct - 1, t, rank * 4 + warp, -1, lane);
      }
      if (threadIdx.x == 256) { PSTAMP(9); PDUMP(8, 9); PDUMP(12, (CL == 8 ? 21 : 43)); PDUMP(28, 43); }
      if (CL == 2 && threadIdx.x == 0) { PDUMP(0, 0); PDUMP(62, 62); }
    } else {
      cluster_wait();
      if (CL == 2 && gemm && warp < 3 && lane == 0) {
        const int src = (j + 1 + warp) & 3;
        const unsigned char* scr = g_pscr + (size_t)(tt * 8 + half * 4 + src) * 40960;
        unsigned int* fl = g_flag + (tt * 8 + half * 4 + src) * 4 + warp;
#pragma unroll 1
        for (int r = 0; r < 5; r++) {
          if (r != 1) mbar_wait(bars + (B_PFREE + (r ? r - 1 : 0)) * 8, 0);
          unsigned int f, it = 0;
          while (true) {
            asm volatile("ld.acquire.gpu.global.u32 %0, [%1];" : "=r"(f) : "l"(fl) : "memory");
            if (f > (unsigned)r) break;
            if (++it > (1u << 22)) __trap();
          }
          asm volatile("fence.proxy.async.global;" ::: "memory");
          bulk_g2s(sb + pslot_off(r, src), scr + r * 8192, 8192, bars + (B_PFULL + r * 4 + src) * 8);
        }
        asm volatile("st.relaxed.gpu.global.u32 [%0], %1;" ::"l"(fl), "r"(0u) : "memory");
      }
    }
  } else {
    if (warp == 0 && lane == 0) {
      if (CL == 8 && noct > 0) {
        const uint32_t lbar = bars + (B_FULL + 4) * 8;
        mbar_expect_tx(lbar, LSET_TX);
#pragma unroll 1
        for (int i = 0; i < P0E; i++) {
          tma3d(sb + OFF_LA + i * LKP, mp.k, toct * 8, rank * 32 - 1, 2 * i, lbar);
          tma3d(i < 3 ? sb + OFF_LA + LV_OFF + i * LVP : sb + OFF_OST, mp.v, toct * 8, rank * 32, 2 * i, lbar);
        }
      }
    } else if (warp == 1 && lane == 0 && gemm) {
      pf_map(half ? &mCi : &mCr); pf_map(&mX);
    }
    if (threadIdx.x == 384) PSTAMP(53);
    __syncwarp();
    asm volatile("setmaxnreg.dec.sync.aligned.u32 72;");
    if (CL == 2 && !gemm) {
      if (warp < 3 && noct > 0) k_builder<CL>(p, sb + OFF_K2 + warp * KBUF, bars + (B_KBAR + warp * 8) * 8, rank, oct0, warp, noct * SEGS, lane);
      else {
        cluster_wait();
        if (noct > 0) {
          mbar_wait(bars + B_DRAIN * 8, 0);
          if (lane == 0) {
#pragma unroll 1
            for (int t = 0; t < noct * 4; t++) {
              mbar_expect_tx(bars + (B_QFULL2 + t) * 8, 4096);
              tma2d(sb + OFF_L2 + t * 4096, mp.q, (oct0 + (t >> 2)) * 8, (rank * 4 + (t & 3)) * 256, bars + (B_QFULL2 + t) * 8);
            }
          }
          __syncwarp();
#pragma unroll 1
          for (int t = 0; t < noct * 4 - 4; t++)
            conv_out<CL>(mp, sb, sb + OFF_L2 + t * 4096, bars + (B_QFULL2 + t) * 8, 0, oct0 + (t >> 2), t, rank * 4 + (t & 3), -1, lane);
        }
      }
    } else if ((warp & 3) == 0) {
      if (lane == 0) PSTAMP(55);
      cluster_wait();
      if (lane == 0) PSTAMP(56);
      if (lane == 0) {
        const CUtensorMap* mC = half ? &mCi : &mCr;
        const CUtensorMap* mW = half ? &mWi : &mWr;
        int s = 0;
        uint32_t ph = 1;
#pragma unroll 1
        for (int k = 0; k < 32; k++) {
          if (k >= 4) mbar_wait(bars + (B_EMPTY + s) * 8, ph);
          const uint32_t fb = bars + (B_FULL + s) * 8, st = sb + (s == 0 ? 4 : s - 1) * STG_BYTES;
          mbar_expect_tx(fb, STG_BYTES);
          if (CL == 8) {
            tma2d_mc(st + j * 4096, mC, k * 64, tt * 128 + j * 32, fb, (uint16_t)(0xF << (4 * half)));
            tma3d_mc(st + A_BYTES + half * (B_BYTES / 2), &mX, 0, k * 64 + 32 * half, j * 5, fb, (uint16_t)(0x11 << j));
          } else {
            tma3d_mc(st + A_BYTES + half * (B_BYTES / 2), &mX, 0, k * 64 + 32 * half, j * 5, fb, (uint16_t)3);
#pragma unroll
            for (int i = 0; i < 4; i++) tma2d(st + i * 4096, mC, k * 64, tt * 128 + i * 32, fb);
          }
          if (++s == NSTG || k == 3) { s = 0; ph ^= 1; }
          if (k == 0) PSTAMP(57);
          if (CL == 8 && noct > 0 && k < 4 - P0E) {
            const uint32_t lbar = bars + (B_FULL + 4) * 8;
            const int i = k + P0E;
            tma3d(sb + OFF_LA + i * LKP, mp.k, toct * 8, rank * 32 - 1, 2 * i, lbar);
            tma3d(i < 3 ? sb + OFF_LA + LV_OFF + i * LVP : sb + OFF_OST, mp.v, toct * 8, rank * 32, 2 * i, lbar);
          }
          if (k == 3) { PSTAMP(58); pf_map(mW); pf_map(&mOa); }
        }
        int ws = 0;
        uint32_t wph = 1;
#pragma unroll 1
        for (int c = 0; c < 20; c++) {
          if (c == 0) mbar_wait(bars + (B_EMPTY + 3) * 8, 1);
          if (c == 3) mbar_wait(bars + (B_EMPTY + 4) * 8, 1);
          if (c == 7) mbar_wait(bars + (B_EMPTY + 0) * 8, 0);
          if (c >= 10) mbar_wait(bars + (B_WEMPTY + ws - 4) * 8, wph);
          const uint32_t fb = bars + (B_WFULL + ws) * 8;
          mbar_expect_tx(fb, W_BYTES);
          const int r = (c - 5) / 3;
          const int col = c < 5 ? j * 160 + c * 32 : ((j + 1 + (c - 5 - 3 * r)) & 3) * 160 + r * 32;
          tma2d(sb + OFF_W + ws * W_BYTES, mW, col, j * 160, fb);
          if (++ws == 10) { ws = 4; wph ^= 1; }
        }
        PDUMP(52, 58);
      }
    } else if (warp > 2) {
      cluster_wait();
      if (lane == 0) {
        unsigned char* scr = g_pscr + (size_t)(tt * 8 + half * 4 + j) * 40960;
        unsigned int* fl = g_flag + (tt * 8 + half * 4 + j) * 4;
        const uint16_t mask = (uint16_t)((0xF ^ (1 << j)) << (4 * half));
        mbar_wait(bars + B_STAGED * 8, 0);
        PSTAMP(26);
        bulk_s2g(scr, sb + OFF_SPY, 8192); bulk_commit();
        mbar_wait(bars + (B_STAGED + 1) * 8, 0);
        bulk_s2g(scr + 8192, sb + j * 8192, 8192); bulk_commit();
        bulk_s2g(scr + 16384, sb + 32768 + j * 8192, 8192); bulk_commit();
        bulk_s2g(scr + 24576, sb + OFF_SPX, 8192); bulk_commit();
#pragma unroll
        for (int r = 0; r < 5; r++) {
          if (r == 0) { bulk_wait<3>(); mbar_arrive(bars + B_C0FREE * 8); PSTAMP(59); }
          if (r == 1) bulk_wait<2>();
          if (r == 2) {
            mbar_wait(bars + (B_STAGED + 2) * 8, 0);
            bulk_s2g(scr + 32768, sb + OFF_SPY, 8192); bulk_commit();
            bulk_wait<2>();
            PSTAMP(60);
          }
          if (r == 3) bulk_wait<1>();
          if (r == 4) { bulk_wait<0>(); PSTAMP(61); }
          if (CL == 8) {
            if (r != 1) mbar_wait(bars + (B_PFREE + (r ? r - 1 : 0)) * 8, 0);
            if (r == 0) PSTAMP(27);
            bulk_g2s_mc(sb + pslot_off(r, j), scr + r * 8192, 8192, bars + (B_PFULL + r * 4 + j) * 8, mask);
          } else {
            asm volatile("fence.proxy.async.global;" ::: "memory");
            asm volatile("fence.acq_rel.gpu;" ::: "memory");
#pragma unroll
            for (int i = 0; i < 3; i++) asm volatile("st.relaxed.gpu.global.u32 [%0], %1;" ::"l"(fl + i), "r"(r + 1) : "memory");
          }
        }
        PDUMP(59, 61); PDUMP(26, 27);
      }
    } else if (warp & 2) {
      if (noct > 0) k_builder<CL>(p, sb + OFF_K, bars + B_KBAR * 8, rank, oct0, 0, noct, lane);
      else cluster_wait();
    } else {
      cluster_wait();
      if (CL == 8 && noct > 0) {
        const uint32_t qb = sb + OFF_OST + 8192, qbar = bars + B_QFULL8 * 8;
        mbar_wait(bars + B_UFULL * 8, 0);
        if (lane == 0) { mbar_expect_tx(qbar, 4096); tma2d(qb, mp.q, oct0 * 8, rank * 256, qbar); }
#pragma unroll 1
        for (int t = 0; t < 5; t++) conv_out<CL>(mp, sb, qb, qbar, t & 1, oct0 + t, t, rank, t < 4 ? oct0 + t + 1 : -1, lane);
        if (lane == 0) { PSTAMP(10); PDUMP(10, 10); }
      }
    }
  }
}

typedef CUresult (*PFN_encodeTiled)(CUtensorMap*, CUtensorMapDataType, cuuint32_t, void*, const cuuint64_t*, const cuuint64_t*, const cuuint32_t*,
                                    const cuuint32_t*, CUtensorMapInterleave, CUtensorMapSwizzle, CUtensorMapL2promotion, CUtensorMapFloatOOBfill);

void make_map(PFN_encodeTiled enc, CUtensorMap* m, const void* ptr, int rank, const cuuint64_t* dims, const cuuint64_t* strides, const cuuint32_t* box,
              CUtensorMapSwizzle swz, CUtensorMapL2promotion prom) {
  cuuint32_t es[5] = {1, 1, 1, 1, 1};
  enc(m, CU_TENSOR_MAP_DATA_TYPE_BFLOAT16, rank, const_cast<void*>(ptr), dims, strides, box, es, CU_TENSOR_MAP_INTERLEAVE_NONE, swz, prom,
      CU_TENSOR_MAP_FLOAT_OOB_FILL_NONE);
}

}

extern "C" void kernel_launch(void* const* d_in, const int* in_sizes, int n_in, void* d_out, int out_size) {
  static PFN_encodeTiled enc = nullptr;
  static int nA = -1;
  cudaStream_t st = cudaStreamPerThread;
  cudaLaunchConfig_t cfg = {};
  cudaLaunchAttribute at[2];
  cfg.blockDim = dim3(512);
  cfg.dynamicSmemBytes = SMEM_BYTES;
  cfg.stream = st;
  cfg.attrs = at;
  at[0].id = cudaLaunchAttributeClusterDimension;
  at[0].val.clusterDim.y = 1;
  at[0].val.clusterDim.z = 1;
  if (nA < 0) {
    void* fn = nullptr;
    cudaDriverEntryPointQueryResult qr;
    cudaGetDriverEntryPoint("cuTensorMapEncodeTiled", &fn, cudaEnableDefault, &qr);
    enc = (PFN_encodeTiled)fn;
    cudaFuncSetAttribute(fused_kernel<8>, cudaFuncAttributeMaxDynamicSharedMemorySize, SMEM_BYTES);
    cudaFuncSetAttribute(fused_kernel<2>, cudaFuncAttributeMaxDynamicSharedMemorySize, SMEM_BYTES);
    int nc = 0;
    cfg.gridDim = dim3(128);
    at[0].val.clusterDim.x = 8;
    cfg.numAttrs = 1;
    if (cudaOccupancyMaxActiveClusters(&nc, fused_kernel<8>, &cfg) != cudaSuccess) nc = 0;
    nA = nc > 16 ? 16 : nc;
  }
  CUtensorMap mCr, mCi, mX, mWr, mWi, mKin, mVin, mQ, mOa, mOb;
  {
    cuuint64_t d[2] = {2048, 2048}, s[1] = {4096};
    cuuint32_t b[2] = {64, 32};
    make_map(enc, &mCr, d_in[1], 2, d, s, b, CU_TENSOR_MAP_SWIZZLE_128B, CU_TENSOR_MAP_L2_PROMOTION_L2_256B);
    make_map(enc, &mCi, d_in[2], 2, d, s, b, CU_TENSOR_MAP_SWIZZLE_128B, CU_TENSOR_MAP_L2_PROMOTION_L2_256B);
  }
  {
    cuuint64_t d[3] = {32, 2048, 20}, s[2] = {1280, 64};
    cuuint32_t b[3] = {32, 32, 5};
    make_map(enc, &mX, d_in[0], 3, d, s, b, CU_TENSOR_MAP_SWIZZLE_64B, CU_TENSOR_MAP_L2_PROMOTION_L2_128B);
  }
  {
    cuuint64_t d[2] = {640, 640}, s[1] = {1280};
    cuuint32_t b[2] = {32, 160};
    make_map(enc, &mWr, d_in[3], 2, d, s, b, CU_TENSOR_MAP_SWIZZLE_64B, CU_TENSOR_MAP_L2_PROMOTION_L2_128B);
    make_map(enc, &mWi, d_in[4], 2, d, s, b, CU_TENSOR_MAP_SWIZZLE_64B, CU_TENSOR_MAP_L2_PROMOTION_L2_128B);
  }
  {
    cuuint64_t d[3] = {640, 256, 8}, s[2] = {10240, 1280};
    cuuint32_t bk[3] = {40, 33, 2}, bv[3] = {40, 32, 2};
    make_map(enc, &mKin, d_in[6], 3, d, s, bk, CU_TENSOR_MAP_SWIZZLE_NONE, CU_TENSOR_MAP_L2_PROMOTION_L2_128B);
    make_map(enc, &mVin, d_in[7], 3, d, s, bv, CU_TENSOR_MAP_SWIZZLE_NONE, CU_TENSOR_MAP_L2_PROMOTION_L2_128B);
  }
  {
    cuuint64_t d[2] = {640, 2048}, s[1] = {1280}, d2[2] = {1280, 2048}, s2[1] = {2560};
    cuuint32_t b[2] = {8, 256}, ba[2] = {80, 16};
    make_map(enc, &mQ, d_in[5], 2, d, s, b, CU_TENSOR_MAP_SWIZZLE_NONE, CU_TENSOR_MAP_L2_PROMOTION_L2_128B);
    make_map(enc, &mOb, d_out, 2, d2, s2, b, CU_TENSOR_MAP_SWIZZLE_NONE, CU_TENSOR_MAP_L2_PROMOTION_NONE);
    make_map(enc, &mOa, d_out, 2, d2, s2, ba, CU_TENSOR_MAP_SWIZZLE_NONE, CU_TENSOR_MAP_L2_PROMOTION_NONE);
  }
  Params p;
  p.x = (const bf16*)d_in[0]; p.cr = (const bf16*)d_in[1]; p.ci = (const bf16*)d_in[2];
  p.shift_k = (const bf16*)d_in[8]; p.ssm_k = (const bf16*)d_in[9]; p.ssm_D = (const bf16*)d_in[10];
  p.nA = nA;
  if (nA > 0) {
    cfg.gridDim = dim3(nA * 8);
    at[0].val.clusterDim.x = 8;
    cfg.numAttrs = 1;
    cudaLaunchKernelEx(&cfg, fused_kernel<8>, mCr, mCi, mX, mWr, mWi, mKin, mVin, mQ, mOa, mOb, p);
  }
  if (nA < 16) {
    cfg.gridDim = dim3((16 - nA) * 12);
    at[0].val.clusterDim.x = 2;
    at[1].id = cudaLaunchAttributeProgrammaticStreamSerialization;
    at[1].val.programmaticStreamSerializationAllowed = 1;
    cfg.numAttrs = nA > 0 ? 2 : 1;
    cudaLaunchKernelEx(&cfg, fused_kernel<2>, mCr, mCi, mX, mWr, mWi, mKin, mVin, mQ, mOa, mOb, p);
  }
}
```

```cpp
#include <cuda_runtime.h>
#include <cuda.h>
#include <cuda_bf16.h>
#include <stdint.h>

#define RG_C 160
#define RG_H 64
namespace {

typedef __nv_bfloat16 bf16;
typedef __nv_bfloat162 bf162;

constexpr int NSTG = 4, A_BYTES = 16384, B_BYTES = 20480, STG_BYTES = A_BYTES + B_BYTES;
constexpr int OFF_D = NSTG * STG_BYTES;
constexpr int W_BYTES = 10240, NW = 9, OFF_SP1 = 32768;
constexpr int OFF_R0 = 2 * STG_BYTES, OFF_SP4 = OFF_R0 + 32768, OFF_R1 = OFF_SP4 + 8192;
constexpr int USLOT = 4608;
constexpr int OFF_U = OFF_D + STG_BYTES + 512;
constexpr int OFF_K = OFF_U + 5 * USLOT;
constexpr int KCH = 576, KE_OFF = 4672, KBUF = 9344;
constexpr int OFF_OST = OFF_K + KBUF;
constexpr int OFF_BAR = OFF_OST + 3 * 4096;
constexpr int OFF_DUMMY = OFF_BAR + 1024 + 512;
constexpr int SMEM_BYTES = OFF_DUMMY + 128;
static_assert(4 * 8704 <= STG_BYTES + 512 && OFF_D + 5 * W_BYTES <= OFF_U + 3 * USLOT && SMEM_BYTES <= 232448, "smem");
constexpr int LKP = 2176, LKB = 1040, LV_OFF = 2 * LKP, LSET = 2 * LV_OFF, LSET_TX = 8 * LKB;
constexpr int OFF_K2 = 12 * USLOT, OFF_OST2 = OFF_K2 + 3 * KBUF, OFF_Q2 = OFF_OST2 + 12 * 4096, OFF_L2 = OFF_BAR - 12 * LSET;
static_assert(OFF_Q2 + 12 * 4096 <= OFF_BAR && OFF_L2 >= OFF_OST2 + 8 * 4096 && OFF_L2 + 4 * LSET >= OFF_Q2 && OFF_OST2 % 128 == 0 && OFF_L2 % 128 == 0, "smem");

enum { B_FULL = 0, B_P0DONE = 4, B_XFREE = 5, B_C1DONE = 6, B_XFULL = 96, B_EMPTY = 8, B_WEMPTY = 112, B_DRAIN = 22, B_R1FREE = 23, B_PFREE = 24, B_STAGED = 32, B_OFREE = 35,
       B_PFULL = 40, B_QFULL8 = 60, B_WFULL = 64, B_OFULL8 = 74, B_KBAR = 80, B_LFULL8 = 88, B_UFREE = 34, B_UFULL = 104, B_OFULL2 = 116, B_QFULL2 = B_PFULL,
       B_LFULL2 = 0 };

struct Params {
  const bf16 *cr, *ci, *ssm_k, *shift_k, *ssm_D;
  unsigned char* pscr;
  unsigned int* flag;
  long long* prof;
  int nA;
};

__device__ __align__(1024) unsigned char g_pscr[16 * 8 * 40960];
__device__ unsigned int g_flag[16 * 8 * 4];
#define PSTAMP(i)
#define PGT(i)
#define PZERO(lo, hi)
#define PQ(a, k)
#define PQD(a)
#define PG(k)
#define PK(a, k)
#define PRAW(i, v)
#define PDUMP(lo, hi)

__device__ __forceinline__ uint32_t smem_u32(const void* p) { return (uint32_t)__cvta_generic_to_shared(p); }
__device__ __forceinline__ uint64_t make_desc(uint32_t saddr, uint32_t lbo, uint32_t sbo, uint32_t swz) {
  return (uint64_t)((saddr & 0x3FFFF) >> 4) | ((uint64_t)(lbo >> 4) << 16) | ((uint64_t)(sbo >> 4) << 32) | ((uint64_t)swz << 62);
}
__device__ __forceinline__ void mbar_init(uint32_t bar, uint32_t cnt) { asm volatile("mbarrier.init.shared::cta.b64 [%0], %1;" ::"r"(bar), "r"(cnt) : "memory"); }
__device__ __forceinline__ void mbar_expect_tx(uint32_t bar, uint32_t bytes) { asm volatile("mbarrier.arrive.expect_tx.shared::cta.b64 _, [%0], %1;" ::"r"(bar), "r"(bytes) : "memory"); }
__device__ __forceinline__ void mbar_arrive(uint32_t bar) { asm volatile("mbarrier.arrive.shared::cta.b64 _, [%0];" ::"r"(bar) : "memory"); }
__device__ __forceinline__ uint32_t mapa(uint32_t a, uint32_t cta) { uint32_t r; asm("mapa.shared::cluster.u32 %0, %1, %2;" : "=r"(r) : "r"(a), "r"(cta)); return r; }
__device__ __forceinline__ void mbar_arrive_rem(uint32_t rbar) { asm volatile("mbarrier.arrive.shared::cluster.b64 _, [%0];" ::"r"(rbar) : "memory"); }
__device__ __forceinline__ void mbar_wait(uint32_t bar, uint32_t parity) {
  asm volatile("{\n.reg .pred p;\n.reg .u32 c;\nmov.u32 c, 0;\nLW:\nmbarrier.try_wait.parity.shared::cta.b64 p, [%0], %1;\n@p bra LD;\n"
               "add.u32 c, c, 1;\nsetp.lt.u32 p, c, 4194304;\n@p bra LW;\ntrap;\nLD:\n}\n" ::"r"(bar), "r"(parity) : "memory");
}
__device__ __forceinline__ bool elect_one() {
  uint32_t r;
  asm volatile("{\n.reg .pred p;\nelect.sync _|p, 0xffffffff;\nselp.u32 %0, 1, 0, p;\n}\n" : "=r"(r));
  return r;
}
__device__ __forceinline__ void tma2d(uint32_t dst, const CUtensorMap* m, int c0, int c1, uint32_t bar) {
  asm volatile("cp.async.bulk.tensor.2d.shared::cluster.global.mbarrier::complete_tx::bytes [%0], [%1, {%3,%4}], [%2];" ::"r"(dst), "l"(m), "r"(bar), "r"(c0), "r"(c1) : "memory");
}
__device__ __forceinline__ void tma2d_mc(uint32_t dst, const CUtensorMap* m, int c0, int c1, uint32_t bar, uint16_t mask) {
  asm volatile("cp.async.bulk.tensor.2d.shared::cluster.global.mbarrier::complete_tx::bytes.multicast::cluster [%0], [%1, {%3,%4}], [%2], %5;" ::"r"(dst), "l"(m), "r"(bar), "r"(c0), "r"(c1), "h"(mask) : "memory");
}
__device__ __forceinline__ void tma3d_mc(uint32_t dst, const CUtensorMap* m, int c0, int c1, int c2, uint32_t bar, uint16_t mask) {
  asm volatile("cp.async.bulk.tensor.3d.shared::cluster.global.mbarrier::complete_tx::bytes.multicast::cluster [%0], [%1, {%3,%4,%5}], [%2], %6;" ::"r"(dst), "l"(m), "r"(bar), "r"(c0), "r"(c1), "r"(c2), "h"(mask) : "memory");
}
__device__ __forceinline__ void tma3d(uint32_t dst, const CUtensorMap* m, int c0, int c1, int c2, uint32_t bar) {
  asm volatile("cp.async.bulk.tensor.3d.shared::cluster.global.mbarrier::complete_tx::bytes [%0], [%1, {%3,%4,%5}], [%2];" ::"r"(dst), "l"(m), "r"(bar), "r"(c0), "r"(c1), "r"(c2) : "memory");
}
__device__ __forceinline__ void tma_store2d(const CUtensorMap* m, uint32_t src, int c0, int c1) {
  asm volatile("cp.async.bulk.tensor.2d.global.shared::cta.bulk_group [%0, {%2,%3}], [%1];" ::"l"(m), "r"(src), "r"(c0), "r"(c1) : "memory");
}
__device__ __forceinline__ void bulk_commit() { asm volatile("cp.async.bulk.commit_group;" ::: "memory"); }
__device__ __forceinline__ void bulk_wait_read() { asm volatile("cp.async.bulk.wait_group.read 0;" ::: "memory"); }
__device__ __forceinline__ void bulk_g2s(uint32_t dst, const void* src, uint32_t bytes, uint32_t bar) {
  asm volatile("cp.async.bulk.shared::cluster.global.mbarrier::complete_tx::bytes [%0], [%1], %2, [%3];" ::"r"(dst), "l"(src), "r"(bytes), "r"(bar) : "memory");
}
__device__ __forceinline__ void bulk_g2s_mc(uint32_t dst, const void* src, uint32_t bytes, uint32_t bar, uint16_t mask) {
  asm volatile("cp.async.bulk.shared::cluster.global.mbarrier::complete_tx::bytes.multicast::cluster [%0], [%1], %2, [%3], %4;" ::"r"(dst), "l"(src), "r"(bytes), "r"(bar), "h"(mask) : "memory");
}
template <int N> __device__ __forceinline__ void bulk_wait() { asm volatile("cp.async.bulk.wait_group %0;" ::"n"(N) : "memory"); }
__device__ __forceinline__ void mbar_arrive_n(uint32_t bar, uint32_t n) { asm volatile("mbarrier.arrive.shared::cta.b64 _, [%0], %1;" ::"r"(bar), "r"(n) : "memory"); }
__device__ __forceinline__ void pf256(uint32_t dummy, const void* p) { asm volatile("cp.async.ca.shared.global.L2::256B [%0], [%1], 4;" ::"r"(dummy), "l"(p) : "memory"); }
__device__ __forceinline__ void pf_map(const CUtensorMap* m) { asm volatile("prefetch.tensormap [%0];" ::"l"(m) : "memory"); }
__device__ __forceinline__ void stsm4(uint32_t a, uint32_t r0, uint32_t r1, uint32_t r2, uint32_t r3) {
  asm volatile("stmatrix.sync.aligned.m8n8.x4.shared.b16 [%0], {%1,%2,%3,%4};" ::"r"(a), "r"(r0), "r"(r1), "r"(r2), "r"(r3) : "memory");
}
__device__ __forceinline__ void bulk_s2g(void* dst, uint32_t src, uint32_t bytes) {
  asm volatile("cp.async.bulk.global.shared::cta.bulk_group [%0], [%1], %2;" ::"l"(dst), "r"(src), "r"(bytes) : "memory");
}
__device__ __forceinline__ void st_async4(uint32_t ra, uint32_t a, uint32_t b, uint32_t c, uint32_t d, uint32_t rbar) {
  asm volatile("st.async.weak.shared::cluster.mbarrier::complete_tx::bytes.v4.b32 [%0], {%1,%2,%3,%4}, [%5];" ::"r"(ra), "r"(a), "r"(b), "r"(c), "r"(d), "r"(rbar) : "memory");
}
__device__ __forceinline__ uint4 lds128(uint32_t a) { uint4 v; asm volatile("ld.shared.v4.u32 {%0,%1,%2,%3}, [%4];" : "=r"(v.x), "=r"(v.y), "=r"(v.z), "=r"(v.w) : "r"(a) : "memory"); return v; }
__device__ __forceinline__ void sts128(uint32_t a, uint32_t x, uint32_t y, uint32_t z, uint32_t w) { asm volatile("st.shared.v4.u32 [%0], {%1,%2,%3,%4};" ::"r"(a), "r"(x), "r"(y), "r"(z), "r"(w) : "memory"); }
__device__ __forceinline__ uint32_t pack_bf16(float lo, float hi) { uint32_t r; asm("cvt.rn.bf16x2.f32 %0, %1, %2;" : "=r"(r) : "f"(hi), "f"(lo)); return r; }
__device__ __forceinline__ uint32_t bmul(uint32_t a, uint32_t b) { uint32_t r; asm("mul.rn.bf16x2 %0, %1, %2;" : "=r"(r) : "r"(a), "r"(b)); return r; }
__device__ __forceinline__ uint32_t bfma(uint32_t a, uint32_t b, uint32_t c) { uint32_t r; asm("fma.rn.bf16x2 %0, %1, %2, %3;" : "=r"(r) : "r"(a), "r"(b), "r"(c)); return r; }
__device__ __forceinline__ uint32_t badd(uint32_t a, uint32_t b) { uint32_t r; asm("add.rn.bf16x2 %0, %1, %2;" : "=r"(r) : "r"(a), "r"(b)); return r; }
__device__ __forceinline__ uint32_t prmt(uint32_t a, uint32_t b, uint32_t s) { uint32_t r; asm("prmt.b32 %0, %1, %2, %3;" : "=r"(r) : "r"(a), "r"(b), "r"(s)); return r; }
__device__ __forceinline__ void fence_async() { asm volatile("fence.proxy.async.shared::cta;" ::: "memory"); }
__device__ __forceinline__ void wg_fence() { asm volatile("wgmma.fence.sync.aligned;" ::: "memory"); }
__device__ __forceinline__ void wg_commit() { asm volatile("wgmma.commit_group.sync.aligned;" ::: "memory"); }
template <int N> __device__ __forceinline__ void wg_wait() { asm volatile("wgmma.wait_group.sync.aligned %0;" ::"n"(N) : "memory"); }
__device__ __forceinline__ void bar_sync(int id, int n) { asm volatile("bar.sync %0, %1;" ::"r"(id), "r"(n) : "memory"); }
__device__ __forceinline__ void cluster_arrive() { asm volatile("barrier.cluster.arrive.relaxed.aligned;" ::: "memory"); }
__device__ __forceinline__ void cluster_wait() { asm volatile("barrier.cluster.wait.acquire.aligned;" ::: "memory"); }

template<int TB,int O,int NA> __device__ __forceinline__ void ss160(float (&c)[NA], uint64_t da, uint64_t db, int sd){
 asm volatile("{\n.reg .pred p;\nsetp.ne.b32 p, %82, 0;\nwgmma.mma_async.sync.aligned.m64n160k16.f32.bf16.bf16 {%0,%1,%2,%3,%4,%5,%6,%7,%8,%9,%10,%11,%12,%13,%14,%15,%16,%17,%18,%19,%20,%21,%22,%23,%24,%25,%26,%27,%28,%29,%30,%31,%32,%33,%34,%35,%36,%37,%38,%39,%40,%41,%42,%43,%44,%45,%46,%47,%48,%49,%50,%51,%52,%53,%54,%55,%56,%57,%58,%59,%60,%61,%62,%63,%64,%65,%66,%67,%68,%69,%70,%71,%72,%73,%74,%75,%76,%77,%78,%79},%80,%81,p,1,1,0,%83;\n}\n"
  : "+f"(c[O+0]),"+f"(c[O+1]),"+f"(c[O+2]),"+f"(c[O+3]),"+f"(c[O+4]),"+f"(c[O+5]),"+f"(c[O+6]),"+f"(c[O+7]),"+f"(c[O+8]),"+f"(c[O+9]),"+f"(c[O+10]),"+f"(c[O+11]),"+f"(c[O+12]),"+f"(c[O+13]),"+f"(c[O+14]),"+f"(c[O+15]),"+f"(c[O+16]),"+f"(c[O+17]),"+f"(c[O+18]),"+f"(c[O+19]),"+f"(c[O+20]),"+f"(c[O+21]),"+f"(c[O+22]),"+f"(c[O+23]),"+f"(c[O+24]),"+f"(c[O+25]),"+f"(c[O+26]),"+f"(c[O+27]),"+f"(c[O+28]),"+f"(c[O+29]),"+f"(c[O+30]),"+f"(c[O+31]),"+f"(c[O+32]),"+f"(c[O+33]),"+f"(c[O+34]),"+f"(c[O+35]),"+f"(c[O+36]),"+f"(c[O+37]),"+f"(c[O+38]),"+f"(c[O+39]),"+f"(c[O+40]),"+f"(c[O+41]),"+f"(c[O+42]),"+f"(c[O+43]),"+f"(c[O+44]),"+f"(c[O+45]),"+f"(c[O+46]),"+f"(c[O+47]),"+f"(c[O+48]),"+f"(c[O+49]),"+f"(c[O+50]),"+f"(c[O+51]),"+f"(c[O+52]),"+f"(c[O+53]),"+f"(c[O+54]),"+f"(c[O+55]),"+f"(c[O+56]),"+f"(c[O+57]),"+f"(c[O+58]),"+f"(c[O+59]),"+f"(c[O+60]),"+f"(c[O+61]),"+f"(c[O+62]),"+f"(c[O+63]),"+f"(c[O+64]),"+f"(c[O+65]),"+f"(c[O+66]),"+f"(c[O+67]),"+f"(c[O+68]),"+f"(c[O+69]),"+f"(c[O+70]),"+f"(c[O+71]),"+f"(c[O+72]),"+f"(c[O+73]),"+f"(c[O+74]),"+f"(c[O+75]),"+f"(c[O+76]),"+f"(c[O+77]),"+f"(c[O+78]),"+f"(c[O+79])
  : "l"(da),"l"(db),"r"(sd),"n"(TB));
}
template<int TB,int O,int NA> __device__ __forceinline__ void ss64(float (&c)[NA], uint64_t da, uint64_t db, int sd){
 asm volatile("{\n.reg .pred p;\nsetp.ne.b32 p, %34, 0;\nwgmma.mma_async.sync.aligned.m64n64k16.f32.bf16.bf16 {%0,%1,%2,%3,%4,%5,%6,%7,%8,%9,%10,%11,%12,%13,%14,%15,%16,%17,%18,%19,%20,%21,%22,%23,%24,%25,%26,%27,%28,%29,%30,%31},%32,%33,p,1,1,0,%35;\n}\n"
  : "+f"(c[O+0]),"+f"(c[O+1]),"+f"(c[O+2]),"+f"(c[O+3]),"+f"(c[O+4]),"+f"(c[O+5]),"+f"(c[O+6]),"+f"(c[O+7]),"+f"(c[O+8]),"+f"(c[O+9]),"+f"(c[O+10]),"+f"(c[O+11]),"+f"(c[O+12]),"+f"(c[O+13]),"+f"(c[O+14]),"+f"(c[O+15]),"+f"(c[O+16]),"+f"(c[O+17]),"+f"(c[O+18]),"+f"(c[O+19]),"+f"(c[O+20]),"+f"(c[O+21]),"+f"(c[O+22]),"+f"(c[O+23]),"+f"(c[O+24]),"+f"(c[O+25]),"+f"(c[O+26]),"+f"(c[O+27]),"+f"(c[O+28]),"+f"(c[O+29]),"+f"(c[O+30]),"+f"(c[O+31])
  : "l"(da),"l"(db),"r"(sd),"n"(TB));
}
template<int TB,int O,int NA> __device__ __forceinline__ void ss96(float (&c)[NA], uint64_t da, uint64_t db, int sd){
 asm volatile("{\n.reg .pred p;\nsetp.ne.b32 p, %50, 0;\nwgmma.mma_async.sync.aligned.m64n96k16.f32.bf16.bf16 {%0,%1,%2,%3,%4,%5,%6,%7,%8,%9,%10,%11,%12,%13,%14,%15,%16,%17,%18,%19,%20,%21,%22,%23,%24,%25,%26,%27,%28,%29,%30,%31,%32,%33,%34,%35,%36,%37,%38,%39,%40,%41,%42,%43,%44,%45,%46,%47},%48,%49,p,1,1,0,%51;\n}\n"
  : "+f"(c[O+0]),"+f"(c[O+1]),"+f"(c[O+2]),"+f"(c[O+3]),"+f"(c[O+4]),"+f"(c[O+5]),"+f"(c[O+6]),"+f"(c[O+7]),"+f"(c[O+8]),"+f"(c[O+9]),"+f"(c[O+10]),"+f"(c[O+11]),"+f"(c[O+12]),"+f"(c[O+13]),"+f"(c[O+14]),"+f"(c[O+15]),"+f"(c[O+16]),"+f"(c[O+17]),"+f"(c[O+18]),"+f"(c[O+19]),"+f"(c[O+20]),"+f"(c[O+21]),"+f"(c[O+22]),"+f"(c[O+23]),"+f"(c[O+24]),"+f"(c[O+25]),"+f"(c[O+26]),"+f"(c[O+27]),"+f"(c[O+28]),"+f"(c[O+29]),"+f"(c[O+30]),"+f"(c[O+31]),"+f"(c[O+32]),"+f"(c[O+33]),"+f"(c[O+34]),"+f"(c[O+35]),"+f"(c[O+36]),"+f"(c[O+37]),"+f"(c[O+38]),"+f"(c[O+39]),"+f"(c[O+40]),"+f"(c[O+41]),"+f"(c[O+42]),"+f"(c[O+43]),"+f"(c[O+44]),"+f"(c[O+45]),"+f"(c[O+46]),"+f"(c[O+47])
  : "l"(da),"l"(db),"r"(sd),"n"(TB));
}
template<int TB,int O,int NA> __device__ __forceinline__ void ss80(float (&c)[NA], uint64_t da, uint64_t db, int sd){
 asm volatile("{\n.reg .pred p;\nsetp.ne.b32 p, %42, 0;\nwgmma.mma_async.sync.aligned.m64n80k16.f32.bf16.bf16 {%0,%1,%2,%3,%4,%5,%6,%7,%8,%9,%10,%11,%12,%13,%14,%15,%16,%17,%18,%19,%20,%21,%22,%23,%24,%25,%26,%27,%28,%29,%30,%31,%32,%33,%34,%35,%36,%37,%38,%39},%40,%41,p,1,1,0,%43;\n}\n"
  : "+f"(c[O+0]),"+f"(c[O+1]),"+f"(c[O+2]),"+f"(c[O+3]),"+f"(c[O+4]),"+f"(c[O+5]),"+f"(c[O+6]),"+f"(c[O+7]),"+f"(c[O+8]),"+f"(c[O+9]),"+f"(c[O+10]),"+f"(c[O+11]),"+f"(c[O+12]),"+f"(c[O+13]),"+f"(c[O+14]),"+f"(c[O+15]),"+f"(c[O+16]),"+f"(c[O+17]),"+f"(c[O+18]),"+f"(c[O+19]),"+f"(c[O+20]),"+f"(c[O+21]),"+f"(c[O+22]),"+f"(c[O+23]),"+f"(c[O+24]),"+f"(c[O+25]),"+f"(c[O+26]),"+f"(c[O+27]),"+f"(c[O+28]),"+f"(c[O+29]),"+f"(c[O+30]),"+f"(c[O+31]),"+f"(c[O+32]),"+f"(c[O+33]),"+f"(c[O+34]),"+f"(c[O+35]),"+f"(c[O+36]),"+f"(c[O+37]),"+f"(c[O+38]),"+f"(c[O+39])
  : "l"(da),"l"(db),"r"(sd),"n"(TB));
}
template<int N> struct RS;
template<> struct RS<160>{ static __device__ __forceinline__ void run(float (&c)[80], const uint32_t* a, uint64_t db, int sd){
 asm volatile("{\n.reg .pred p;\nsetp.ne.b32 p, %85, 0;\nwgmma.mma_async.sync.aligned.m64n160k16.f32.bf16.bf16 {%0,%1,%2,%3,%4,%5,%6,%7,%8,%9,%10,%11,%12,%13,%14,%15,%16,%17,%18,%19,%20,%21,%22,%23,%24,%25,%26,%27,%28,%29,%30,%31,%32,%33,%34,%35,%36,%37,%38,%39,%40,%41,%42,%43,%44,%45,%46,%47,%48,%49,%50,%51,%52,%53,%54,%55,%56,%57,%58,%59,%60,%61,%62,%63,%64,%65,%66,%67,%68,%69,%70,%71,%72,%73,%74,%75,%76,%77,%78,%79},{%80,%81,%82,%83},%84,p,1,1,0;\n}\n"
  : "+f"(c[0]),"+f"(c[1]),"+f"(c[2]),"+f"(c[3]),"+f"(c[4]),"+f"(c[5]),"+f"(c[6]),"+f"(c[7]),"+f"(c[8]),"+f"(c[9]),"+f"(c[10]),"+f"(c[11]),"+f"(c[12]),"+f"(c[13]),"+f"(c[14]),"+f"(c[15]),"+f"(c[16]),"+f"(c[17]),"+f"(c[18]),"+f"(c[19]),"+f"(c[20]),"+f"(c[21]),"+f"(c[22]),"+f"(c[23]),"+f"(c[24]),"+f"(c[25]),"+f"(c[26]),"+f"(c[27]),"+f"(c[28]),"+f"(c[29]),"+f"(c[30]),"+f"(c[31]),"+f"(c[32]),"+f"(c[33]),"+f"(c[34]),"+f"(c[35]),"+f"(c[36]),"+f"(c[37]),"+f"(c[38]),"+f"(c[39]),"+f"(c[40]),"+f"(c[41]),"+f"(c[42]),"+f"(c[43]),"+f"(c[44]),"+f"(c[45]),"+f"(c[46]),"+f"(c[47]),"+f"(c[48]),"+f"(c[49]),"+f"(c[50]),"+f"(c[51]),"+f"(c[52]),"+f"(c[53]),"+f"(c[54]),"+f"(c[55]),"+f"(c[56]),"+f"(c[57]),"+f"(c[58]),"+f"(c[59]),"+f"(c[60]),"+f"(c[61]),"+f"(c[62]),"+f"(c[63]),"+f"(c[64]),"+f"(c[65]),"+f"(c[66]),"+f"(c[67]),"+f"(c[68]),"+f"(c[69]),"+f"(c[70]),"+f"(c[71]),"+f"(c[72]),"+f"(c[73]),"+f"(c[74]),"+f"(c[75]),"+f"(c[76]),"+f"(c[77]),"+f"(c[78]),"+f"(c[79])
  : "r"(a[0]),"r"(a[1]),"r"(a[2]),"r"(a[3]),"l"(db),"r"(sd));
}
 static __device__ __forceinline__ void first(float (&c)[80], const uint32_t* a, uint64_t db){
 asm volatile("{\n.reg .pred p;\nsetp.ne.b32 p, 0, 0;\nwgmma.mma_async.sync.aligned.m64n160k16.f32.bf16.bf16 {%0,%1,%2,%3,%4,%5,%6,%7,%8,%9,%10,%11,%12,%13,%14,%15,%16,%17,%18,%19,%20,%21,%22,%23,%24,%25,%26,%27,%28,%29,%30,%31,%32,%33,%34,%35,%36,%37,%38,%39,%40,%41,%42,%43,%44,%45,%46,%47,%48,%49,%50,%51,%52,%53,%54,%55,%56,%57,%58,%59,%60,%61,%62,%63,%64,%65,%66,%67,%68,%69,%70,%71,%72,%73,%74,%75,%76,%77,%78,%79},{%80,%81,%82,%83},%84,p,1,1,0;\n}\n"
  : "=f"(c[0]),"=f"(c[1]),"=f"(c[2]),"=f"(c[3]),"=f"(c[4]),"=f"(c[5]),"=f"(c[6]),"=f"(c[7]),"=f"(c[8]),"=f"(c[9]),"=f"(c[10]),"=f"(c[11]),"=f"(c[12]),"=f"(c[13]),"=f"(c[14]),"=f"(c[15]),"=f"(c[16]),"=f"(c[17]),"=f"(c[18]),"=f"(c[19]),"=f"(c[20]),"=f"(c[21]),"=f"(c[22]),"=f"(c[23]),"=f"(c[24]),"=f"(c[25]),"=f"(c[26]),"=f"(c[27]),"=f"(c[28]),"=f"(c[29]),"=f"(c[30]),"=f"(c[31]),"=f"(c[32]),"=f"(c[33]),"=f"(c[34]),"=f"(c[35]),"=f"(c[36]),"=f"(c[37]),"=f"(c[38]),"=f"(c[39]),"=f"(c[40]),"=f"(c[41]),"=f"(c[42]),"=f"(c[43]),"=f"(c[44]),"=f"(c[45]),"=f"(c[46]),"=f"(c[47]),"=f"(c[48]),"=f"(c[49]),"=f"(c[50]),"=f"(c[51]),"=f"(c[52]),"=f"(c[53]),"=f"(c[54]),"=f"(c[55]),"=f"(c[56]),"=f"(c[57]),"=f"(c[58]),"=f"(c[59]),"=f"(c[60]),"=f"(c[61]),"=f"(c[62]),"=f"(c[63]),"=f"(c[64]),"=f"(c[65]),"=f"(c[66]),"=f"(c[67]),"=f"(c[68]),"=f"(c[69]),"=f"(c[70]),"=f"(c[71]),"=f"(c[72]),"=f"(c[73]),"=f"(c[74]),"=f"(c[75]),"=f"(c[76]),"=f"(c[77]),"=f"(c[78]),"=f"(c[79])
  : "r"(a[0]),"r"(a[1]),"r"(a[2]),"r"(a[3]),"l"(db));
}
};
template<> struct RS<32>{ static __device__ __forceinline__ void run(float (&c)[64], const uint32_t* a, uint64_t db, int sd){
 asm volatile("{\n.reg .pred p;\nsetp.ne.b32 p, %21, 0;\nwgmma.mma_async.sync.aligned.m64n32k16.f32.bf16.bf16 {%0,%1,%2,%3,%4,%5,%6,%7,%8,%9,%10,%11,%12,%13,%14,%15},{%16,%17,%18,%19},%20,p,1,1,0;\n}\n"
  : "+f"(c[0]),"+f"(c[1]),"+f"(c[2]),"+f"(c[3]),"+f"(c[4]),"+f"(c[5]),"+f"(c[6]),"+f"(c[7]),"+f"(c[8]),"+f"(c[9]),"+f"(c[10]),"+f"(c[11]),"+f"(c[12]),"+f"(c[13]),"+f"(c[14]),"+f"(c[15])
  : "r"(a[0]),"r"(a[1]),"r"(a[2]),"r"(a[3]),"l"(db),"r"(sd));
}
};
template<> struct RS<64>{ static __device__ __forceinline__ void run(float (&c)[64], const uint32_t* a, uint64_t db, int sd){
 asm volatile("{\n.reg .pred p;\nsetp.ne.b32 p, %37, 0;\nwgmma.mma_async.sync.aligned.m64n64k16.f32.bf16.bf16 {%0,%1,%2,%3,%4,%5,%6,%7,%8,%9,%10,%11,%12,%13,%14,%15,%16,%17,%18,%19,%20,%21,%22,%23,%24,%25,%26,%27,%28,%29,%30,%31},{%32,%33,%34,%35},%36,p,1,1,0;\n}\n"
  : "+f"(c[0]),"+f"(c[1]),"+f"(c[2]),"+f"(c[3]),"+f"(c[4]),"+f"(c[5]),"+f"(c[6]),"+f"(c[7]),"+f"(c[8]),"+f"(c[9]),"+f"(c[10]),"+f"(c[11]),"+f"(c[12]),"+f"(c[13]),"+f"(c[14]),"+f"(c[15]),"+f"(c[16]),"+f"(c[17]),"+f"(c[18]),"+f"(c[19]),"+f"(c[20]),"+f"(c[21]),"+f"(c[22]),"+f"(c[23]),"+f"(c[24]),"+f"(c[25]),"+f"(c[26]),"+f"(c[27]),"+f"(c[28]),"+f"(c[29]),"+f"(c[30]),"+f"(c[31])
  : "r"(a[0]),"r"(a[1]),"r"(a[2]),"r"(a[3]),"l"(db),"r"(sd));
}
};
template<> struct RS<96>{ static __device__ __forceinline__ void run(float (&c)[64], const uint32_t* a, uint64_t db, int sd){
 asm volatile("{\n.reg .pred p;\nsetp.ne.b32 p, %53, 0;\nwgmma.mma_async.sync.aligned.m64n96k16.f32.bf16.bf16 {%0,%1,%2,%3,%4,%5,%6,%7,%8,%9,%10,%11,%12,%13,%14,%15,%16,%17,%18,%19,%20,%21,%22,%23,%24,%25,%26,%27,%28,%29,%30,%31,%32,%33,%34,%35,%36,%37,%38,%39,%40,%41,%42,%43,%44,%45,%46,%47},{%48,%49,%50,%51},%52,p,1,1,0;\n}\n"
  : "+f"(c[0]),"+f"(c[1]),"+f"(c[2]),"+f"(c[3]),"+f"(c[4]),"+f"(c[5]),"+f"(c[6]),"+f"(c[7]),"+f"(c[8]),"+f"(c[9]),"+f"(c[10]),"+f"(c[11]),"+f"(c[12]),"+f"(c[13]),"+f"(c[14]),"+f"(c[15]),"+f"(c[16]),"+f"(c[17]),"+f"(c[18]),"+f"(c[19]),"+f"(c[20]),"+f"(c[21]),"+f"(c[22]),"+f"(c[23]),"+f"(c[24]),"+f"(c[25]),"+f"(c[26]),"+f"(c[27]),"+f"(c[28]),"+f"(c[29]),"+f"(c[30]),"+f"(c[31]),"+f"(c[32]),"+f"(c[33]),"+f"(c[34]),"+f"(c[35]),"+f"(c[36]),"+f"(c[37]),"+f"(c[38]),"+f"(c[39]),"+f"(c[40]),"+f"(c[41]),"+f"(c[42]),"+f"(c[43]),"+f"(c[44]),"+f"(c[45]),"+f"(c[46]),"+f"(c[47])
  : "r"(a[0]),"r"(a[1]),"r"(a[2]),"r"(a[3]),"l"(db),"r"(sd));
}
};
template<> struct RS<128>{ static __device__ __forceinline__ void run(float (&c)[64], const uint32_t* a, uint64_t db, int sd){
 asm volatile("{\n.reg .pred p;\nsetp.ne.b32 p, %69, 0;\nwgmma.mma_async.sync.aligned.m64n128k16.f32.bf16.bf16 {%0,%1,%2,%3,%4,%5,%6,%7,%8,%9,%10,%11,%12,%13,%14,%15,%16,%17,%18,%19,%20,%21,%22,%23,%24,%25,%26,%27,%28,%29,%30,%31,%32,%33,%34,%35,%36,%37,%38,%39,%40,%41,%42,%43,%44,%45,%46,%47,%48,%49,%50,%51,%52,%53,%54,%55,%56,%57,%58,%59,%60,%61,%62,%63},{%64,%65,%66,%67},%68,p,1,1,0;\n}\n"
  : "+f"(c[0]),"+f"(c[1]),"+f"(c[2]),"+f"(c[3]),"+f"(c[4]),"+f"(c[5]),"+f"(c[6]),"+f"(c[7]),"+f"(c[8]),"+f"(c[9]),"+f"(c[10]),"+f"(c[11]),"+f"(c[12]),"+f"(c[13]),"+f"(c[14]),"+f"(c[15]),"+f"(c[16]),"+f"(c[17]),"+f"(c[18]),"+f"(c[19]),"+f"(c[20]),"+f"(c[21]),"+f"(c[22]),"+f"(c[23]),"+f"(c[24]),"+f"(c[25]),"+f"(c[26]),"+f"(c[27]),"+f"(c[28]),"+f"(c[29]),"+f"(c[30]),"+f"(c[31]),"+f"(c[32]),"+f"(c[33]),"+f"(c[34]),"+f"(c[35]),"+f"(c[36]),"+f"(c[37]),"+f"(c[38]),"+f"(c[39]),"+f"(c[40]),"+f"(c[41]),"+f"(c[42]),"+f"(c[43]),"+f"(c[44]),"+f"(c[45]),"+f"(c[46]),"+f"(c[47]),"+f"(c[48]),"+f"(c[49]),"+f"(c[50]),"+f"(c[51]),"+f"(c[52]),"+f"(c[53]),"+f"(c[54]),"+f"(c[55]),"+f"(c[56]),"+f"(c[57]),"+f"(c[58]),"+f"(c[59]),"+f"(c[60]),"+f"(c[61]),"+f"(c[62]),"+f"(c[63])
  : "r"(a[0]),"r"(a[1]),"r"(a[2]),"r"(a[3]),"l"(db),"r"(sd));
}
 static __device__ __forceinline__ void first(float (&c)[64], const uint32_t* a, uint64_t db){
 asm volatile("{\n.reg .pred p;\nsetp.ne.b32 p, 0, 0;\nwgmma.mma_async.sync.aligned.m64n128k16.f32.bf16.bf16 {%0,%1,%2,%3,%4,%5,%6,%7,%8,%9,%10,%11,%12,%13,%14,%15,%16,%17,%18,%19,%20,%21,%22,%23,%24,%25,%26,%27,%28,%29,%30,%31,%32,%33,%34,%35,%36,%37,%38,%39,%40,%41,%42,%43,%44,%45,%46,%47,%48,%49,%50,%51,%52,%53,%54,%55,%56,%57,%58,%59,%60,%61,%62,%63},{%64,%65,%66,%67},%68,p,1,1,0;\n}\n"
  : "=f"(c[0]),"=f"(c[1]),"=f"(c[2]),"=f"(c[3]),"=f"(c[4]),"=f"(c[5]),"=f"(c[6]),"=f"(c[7]),"=f"(c[8]),"=f"(c[9]),"=f"(c[10]),"=f"(c[11]),"=f"(c[12]),"=f"(c[13]),"=f"(c[14]),"=f"(c[15]),"=f"(c[16]),"=f"(c[17]),"=f"(c[18]),"=f"(c[19]),"=f"(c[20]),"=f"(c[21]),"=f"(c[22]),"=f"(c[23]),"=f"(c[24]),"=f"(c[25]),"=f"(c[26]),"=f"(c[27]),"=f"(c[28]),"=f"(c[29]),"=f"(c[30]),"=f"(c[31]),"=f"(c[32]),"=f"(c[33]),"=f"(c[34]),"=f"(c[35]),"=f"(c[36]),"=f"(c[37]),"=f"(c[38]),"=f"(c[39]),"=f"(c[40]),"=f"(c[41]),"=f"(c[42]),"=f"(c[43]),"=f"(c[44]),"=f"(c[45]),"=f"(c[46]),"=f"(c[47]),"=f"(c[48]),"=f"(c[49]),"=f"(c[50]),"=f"(c[51]),"=f"(c[52]),"=f"(c[53]),"=f"(c[54]),"=f"(c[55]),"=f"(c[56]),"=f"(c[57]),"=f"(c[58]),"=f"(c[59]),"=f"(c[60]),"=f"(c[61]),"=f"(c[62]),"=f"(c[63])
  : "r"(a[0]),"r"(a[1]),"r"(a[2]),"r"(a[3]),"l"(db));
}
};

struct Maps { const CUtensorMap *k, *v, *q, *ob; };
__device__ __forceinline__ void p0_issue(const Maps& m, uint32_t lb, uint32_t bar, int oct, int row0, int b) {
  tma3d(lb + (b & 1) * LV_OFF + (b >> 1) * LKP, (b & 1) ? m.v : m.k, oct * 8, (row0 >> 2) - 1, b & 2, bar);
}
__device__ __forceinline__ uint2 ldg64c(const void* p) { uint2 v; asm volatile("ld.global.nc.v2.u32 {%0,%1}, [%2];" : "=r"(v.x), "=r"(v.y) : "l"(p)); return v; }
__device__ __forceinline__ uint2 p0_w(const Params& p, int oct, int lane) { return ldg64c(p.shift_k + oct * 32 + (lane >> 2) * 4); }
__device__ __forceinline__ void ldsm4t(uint32_t* r, uint32_t a) {
  asm volatile("ldmatrix.sync.aligned.m8n8.x4.trans.shared.b16 {%0,%1,%2,%3}, [%4];" : "=r"(r[0]), "=r"(r[1]), "=r"(r[2]), "=r"(r[3]) : "r"(a) : "memory");
}
template <int CL, int NIT>
__device__ __forceinline__ void p0_task(uint2 w, uint32_t sb, uint32_t ubase, uint32_t lb, uint32_t bar, int ol, int row0, int it0, int lane) {
  constexpr int CPC = 8 / CL;
  const int ch = lane >> 2, slot = ol * CPC + ch % CPC;
  uint32_t ua = mapa(ubase + slot * USLOT + 4080 - 2 * row0 - 64 * it0 - 16 * ((lane & 3) ^ ((~it0 >> 1) & 1)), ch / CPC);
  const uint32_t ub = mapa(sb + OFF_BAR + (B_UFULL + slot) * 8, ch / CPC);
  uint32_t la[2];
#pragma unroll
  for (int t = 0; t < 2; t++) {
    const int r = 8 * ((lane >> 1) & 3) + 11 - 2 * ((lane >> 3) & (t ? 1 : 3)) - (lane & 1) - 8 * t;
    la[t] = lb + it0 * 128 + ((r >> 1) & 1) * LKP + (r & 1) * LKB + (r >> 2) * 16;
  }
  const uint32_t w0 = prmt(w.x, 0, 0x1010), w1 = prmt(w.x, 0, 0x3232), w2 = prmt(w.y, 0, 0x1010), w3 = prmt(w.y, 0, 0x3232);
  mbar_wait(bar, 0);
  if (CL == 8 && threadIdx.x == 256) PSTAMP(41);
#pragma unroll
  for (int i = 0; i < NIT; i++) {
    uint32_t k[6], o[5], v[4];
    ldsm4t(k, la[0] + i * 128);
    asm volatile("ldmatrix.sync.aligned.m8n8.x2.trans.shared.b16 {%0,%1}, [%2];" : "=r"(k[4]), "=r"(k[5]) : "r"(la[1] + i * 128) : "memory");
    ldsm4t(v, la[0] + i * 128 + LV_OFF);
#pragma unroll
    for (int m = 0; m < 5; m++) o[m] = prmt(k[m], k[m + 1], 0x5432);
#pragma unroll
    for (int m = 0; m < 4; m++) v[m] = bmul(bfma(k[m], w0, bfma(o[m], w1, bfma(k[m + 1], w2, bmul(o[m + 1], w3)))), v[m]);
    st_async4(ua, v[0], v[1], v[2], v[3], ub);
    ua = (i & 1) ? (ua ^ 16) - 64 : ua - 64;
  }
}

template <int CL>
__device__ __forceinline__ uint32_t ost_addr(uint32_t sb, int task) {
  if (CL == 8) return sb + OFF_OST + (task & 1) * 4096;
  return sb + OFF_OST2 + task * 4096;
}

template <int CL>
__device__ __forceinline__ void conv_out(const Maps& mp, uint32_t sb, uint32_t qbuf, uint32_t qbar, uint32_t qpar, int oct, int task, int seg,
                                         int next_oct, int lane) {
  const uint32_t ya = ost_addr<CL>(sb, task) + (lane >> 2) * 512 + (lane & 3) * 16, yx = (lane & 4) * 16;
  const uint32_t qa = qbuf + 4080 - 16 * lane;
  mbar_wait(sb + OFF_BAR + ((CL == 8 ? B_OFULL8 : B_OFULL2) + task) * 8, 0);
  mbar_wait(qbar, qpar);
#pragma unroll
  for (int h = 0; h < 2; h++) {
    uint4 y[4];
    uint32_t qv[4][4];
#pragma unroll
    for (int i = 0; i < 4; i++) {
      y[i] = lds128((i & 1 ? ya - yx : ya + yx) + h * 256 + i * 64);
      ldsm4t(qv[i], qa - h * 2048 - i * 512);
    }
#pragma unroll
    for (int i = 0; i < 4; i++)
      asm volatile("stmatrix.sync.aligned.m8n8.x4.trans.shared.b16 [%0], {%1,%2,%3,%4};" ::"r"(qa - h * 2048 - i * 512), "r"(bmul(qv[i][0], y[i].x)),
                   "r"(bmul(qv[i][1], y[i].y)), "r"(bmul(qv[i][2], y[i].z)), "r"(bmul(qv[i][3], y[i].w)) : "memory");
  }
  fence_async();
  __syncwarp();
  if (CL == 8 && task < 3 && lane < 8) mbar_arrive_rem(mapa(sb + OFF_BAR + (B_OFREE + task) * 8, lane));
  if (lane == 0) {
    asm volatile("cp.async.bulk.tensor.3d.global.shared::cta.bulk_group [%0, {%2,%3,%4}], [%1];" ::"l"(mp.ob), "r"(qbuf), "r"(640 + oct * 8), "r"(seg * 16), "r"(0) : "memory");
    bulk_commit();
    bulk_wait_read();
    if (next_oct >= 0) { mbar_expect_tx(qbar, 4096); tma3d(qbuf, mp.q, next_oct * 8, seg * 16, 0, qbar); }
  }
  __syncwarp();
}

struct KRegs { uint2 f[8], s[8]; uint32_t d; };
__device__ __forceinline__ void k_load(const Params& p, KRegs& r, int ch, int lane) {
  const bf16* src = p.ssm_k + (size_t)ch * 2048 + lane * 4;
  r.d = lane ? 0u : __ldg((const unsigned short*)(p.ssm_D + ch));
#pragma unroll
  for (int i = 0; i < 8; i++) {
    r.f[i] = ldg64c(src + i * 256);
    r.s[i] = ldg64c(src + i * 256 + 128);
  }
}
template <int CL>
__device__ __forceinline__ void k_builder(const Params& p, KRegs& r, uint32_t kbase, uint32_t kbar, int rank, int oct0, int first, int nch, int lane) {
  constexpr int CPC = 8 / CL, STEP = CL == 8 ? 1 : 3;
  int it = 0;
  const uint32_t o = kbase + 64 + lane * 16;
  cluster_wait();
#pragma unroll 1
  for (int ci = first; ci < nch; ci += STEP, it++) {
    if (it > 0) k_load(p, r, (oct0 + 16 * (ci / CPC)) * 8 + rank * CPC + ci % CPC, lane);
    r.f[0].x = badd(r.f[0].x, r.d);
    uint32_t pp = 0, hx = 0, hy = 0;
#pragma unroll
    for (int i = 0; i < 8; i++) {
      if (it > 0 && !(i & 1)) mbar_wait(kbar + (4 + (i >> 1)) * 8, (it - 1) & 1);
      const uint2 f = r.f[i], g = r.s[i];
      const uint32_t p1 = __shfl_sync(0xffffffffu, f.y, lane - 1), p2 = __shfl_sync(0xffffffffu, g.y, lane - 1);
      const uint32_t fx = __funnelshift_l(lane ? p1 : pp, f.x, 16), fy = __funnelshift_l(f.x, f.y, 16);
      const uint32_t gx = __funnelshift_l(lane ? p2 : p1, g.x, 16), gy = __funnelshift_l(g.x, g.y, 16);
      sts128(o + i * KCH + KE_OFF, f.x, g.x, f.y, g.y);
      sts128(o + i * KCH, fx, gx, fy, gy);
      if (lane >= 28) {
        sts128(o + i * KCH + KE_OFF - 512, i ? r.s[i ? i - 1 : 0].x : 0, f.x, i ? r.s[i ? i - 1 : 0].y : 0, f.y);
        sts128(o + i * KCH - 512, hx, fx, hy, fy);
      }
      pp = p2; hx = gx; hy = gy;
      if (i & 1) {
        __syncwarp();
        if (lane == 0) mbar_arrive_n(kbar + (i >> 1) * 8, 4);
      }
    }
  }
}

__device__ __forceinline__ void load_a(uint32_t* a, uint32_t ka) {
#pragma unroll
  for (int i = 0; i < 8; i++) asm volatile("ld.shared.v2.u32 {%0,%1}, [%2];" : "=r"(a[2 * i]), "=r"(a[2 * i + 1]) : "r"(ka + 32 * i));
}
struct Ret { float keep[4], send[4], car[4]; };
template <int A>
__device__ __forceinline__ void conv_sums(Ret& t, const float (&c)[64], uint32_t gb) {
  constexpr int J0 = 12 - 4 * A;
#pragma unroll
  for (int i = 0; i < 4; i++) {
    const int j = J0 + (i >> 1), e = i & 1;
    const float lo = c[4 * j + e] + c[4 * j + 6 + e];
    t.send[i] = j + 2 == 15 ? c[4 * j + 8 + e] : c[4 * j + 8 + e] + c[(4 * j + 14 + e) & 63];
    t.keep[i] = gb ? (A == 0 ? 0.f : t.car[i]) : lo;
    t.car[i] = lo;
    asm volatile("" : "+f"(t.keep[i]), "+f"(t.send[i]), "+f"(t.car[i])::"memory");
  }
}
__device__ __forceinline__ void conv_finish(Ret& t, uint32_t ra, uint32_t rb, uint32_t en) {
  float y[4];
#pragma unroll
  for (int i = 0; i < 4; i++) y[i] = t.keep[i] + __shfl_xor_sync(0xffffffffu, t.send[i], 16);
  asm volatile("{\n.reg .pred p;\nsetp.ne.u32 p, %4, 0;\n@p st.async.weak.shared::cluster.mbarrier::complete_tx::bytes.v2.b32 [%0], {%1,%2}, [%3];\n}\n" ::"r"(ra),
               "r"(pack_bf16(y[0], y[1])), "r"(pack_bf16(y[2], y[3])), "r"(rb), "r"(en) : "memory");
}
template <int A>
__device__ __forceinline__ void conv_burst(float (&c)[64], const uint32_t (&a)[32], uint64_t d0) {
  constexpr int N = 128 - 32 * A;
  if (A > 0) {
#pragma unroll
    for (int i = 0; i < N / 2; i++) asm volatile("mov.b32 %0, %1;" : "=f"(c[i]) : "f"(c[i]) : "memory");
  }
  wg_fence();
  if constexpr (A == 0) RS<128>::first(c, &a[0], d0);
  else RS<N>::run(c, &a[0], d0 + 64 * A, 1);
#pragma unroll
  for (int i = 1; i < 8; i++) {
    RS<N>::run(c, &a[4 * i], d0 + 64 * A + 2 * i, 1);
    if (i == 3) wg_commit();
  }
  wg_commit();
}

template <int CL>
__device__ __forceinline__ void conv_main(uint32_t sb, uint32_t ubase, uint32_t kbase, uint32_t kbar, int rank, int first, int nch, int tid) {
  constexpr int CPC = 8 / CL, STEP = CL == 8 ? 1 : 3, SEGS = 8 / CL;
  const int lane = tid & 31, w = tid >> 5, g = lane >> 2, q = lane & 3, rho = 4 * w + (g & 3);
  const uint32_t gb = g >> 2;
  const uint32_t ka = kbase + ((g & 1) ? 0 : KE_OFF) + gb * KCH + 64 + 8 * (q - (rho >> 1));
  const uint32_t oa0 = mapa(sb + (CL == 8 ? OFF_OST : OFF_OST2 + (1 - gb) * 4096) + ((rho >> 1) * 4 + q) * 16 + (rho & 1) * 8, CL == 8 ? 1 - gb : 0);
  const uint32_t ob0 = mapa(sb + OFF_BAR + (CL == 8 ? B_OFULL8 : B_OFULL2 + 1 - gb) * 8, CL == 8 ? 1 - gb : 0);
  constexpr uint32_t OA1 = CL == 8 ? 2u << 24 : 8192, OB1 = CL == 8 ? 2u << 24 : 16, OA2 = CL == 8 ? 4u << 24 : 1u << 24;
  float c[64];
  Ret t;
#pragma unroll
  for (int i = 0; i < 4; i++) t.keep[i] = t.send[i] = t.car[i] = 0.f;
  uint32_t a[32];
  uint32_t poa = oa0, pob = ob0, par = 0;
  mbar_wait(kbar, 0);
  load_a(a, ka);
  load_a(a + 16, ka + 256);
#pragma unroll 1
  for (int ci = first; ci < nch; ci += STEP) {
    const int oloc = ci / CPC, chi = rank * CPC + ci % CPC;
    const bool more = ci + STEP < nch;
    const uint32_t uslot = ubase + ci * USLOT;
    const uint32_t oa = (oa0 ^ ((chi & 1) << 6)) + (CL == 8 ? (oloc & 1) * 4096 : oloc * SEGS * 4096) + chi * 512, ob = ob0 + oloc * SEGS * 8;
    const uint64_t d0 = make_desc(uslot, 16, 256, 3);
    if (tid == 0) PSTAMP(12 + 2 * ci);
    mbar_wait(sb + OFF_BAR + (B_UFULL + ci) * 8, 0);
    if (CL == 8 && ci == 4) mbar_wait(sb + OFF_BAR + B_STAGED * 8, 0);
    fence_async();
    if (tid == 0) PSTAMP(13 + 2 * ci);
    conv_burst<0>(c, a, d0);
    if (more && lane == 0) mbar_arrive(kbar + 32);
    mbar_wait(kbar + 8, par);
    wg_wait<1>();
    load_a(a, ka + 2 * KCH);
    conv_finish(t, poa + OA2 + OA1, pob + OA2 + OB1, ci > first);
    wg_wait<0>();
    load_a(a + 16, ka + 2 * KCH + 256);
    conv_sums<0>(t, c, gb);
    conv_burst<1>(c, a, d0);
    if (more && lane == 0) mbar_arrive(kbar + 40);
    mbar_wait(kbar + 16, par);
    wg_wait<1>();
    load_a(a, ka + 4 * KCH);
    if (CL == 8 && ci >= 2) mbar_wait(sb + OFF_BAR + (B_OFREE + ci - 2) * 8, 0);
    conv_finish(t, oa, ob, 1);
    wg_wait<0>();
    load_a(a + 16, ka + 4 * KCH + 256);
    conv_sums<1>(t, c, gb);
    conv_burst<2>(c, a, d0);
    if (more && lane == 0) mbar_arrive(kbar + 48);
    mbar_wait(kbar + 24, par);
    wg_wait<1>();
    load_a(a, ka + 6 * KCH);
    conv_finish(t, oa + OA1, ob + OB1, 1);
    wg_wait<0>();
    load_a(a + 16, ka + 6 * KCH + 256);
    conv_sums<2>(t, c, gb);
    conv_burst<3>(c, a, d0);
    if (more && lane == 0) mbar_arrive(kbar + 56);
    mbar_wait(kbar, more ? par ^ 1 : par);
    wg_wait<1>();
    load_a(a, ka);
    conv_finish(t, oa + OA2, ob + OA2, 1);
    wg_wait<0>();
    load_a(a + 16, ka + 256);
    if (CL == 8 && ci == 2 && lane == 0) mbar_arrive_n(sb + OFF_BAR + B_UFREE * 8, 2);
    conv_sums<3>(t, c, gb);
    poa = oa; pob = ob; par ^= 1;
  }
  conv_finish(t, poa + OA2 + OA1, pob + OA2 + OB1, 1);
}

template <int V> struct IC { static constexpr int value = V; };
__device__ __forceinline__ uint32_t pslot_off(int r, int src) { return (r % 3 == 0 ? 0 : r % 3 == 1 ? OFF_R0 : OFF_R1) + src * 8192; }
__device__ __forceinline__ uint32_t stg_off(int r, int j) { return r == 0 ? j * 8192 : r == 1 ? OFF_SP1 : r == 2 ? OFF_R0 + j * 8192 : r == 3 ? OFF_SP4 : OFF_R1 + j * 8192; }
__device__ __forceinline__ uint32_t w_off(int s) { return s < 5 ? OFF_D + s * W_BYTES : OFF_SP1 + (8 - s) * W_BYTES; }

template <int CL>
__device__ __forceinline__ void gemm_consumer(const CUtensorMap* mOa, uint32_t sb, int wg, int tid, int rank, int half, int j, int tt) {
  const int lane = tid & 31, w = tid >> 5;
  const uint32_t bars = sb + OFF_BAR;
  constexpr int NREL = CL == 8 ? 5 : 2;
  uint32_t rel = 0;
  if (tid < NREL) {
    int tgt = CL == 8 ? (tid < 4 ? half * 4 + tid : rank ^ 4) : tid;
    rel = mapa(bars + B_EMPTY * 8, tgt);
  }
  asm volatile("setmaxnreg.inc.sync.aligned.u32 %0;" ::"n"(RG_C));
  uint32_t bv = bars;
  asm volatile("" : "+r"(bv));
  float acc[80];
#pragma unroll
  for (int i = 0; i < 80; i++) acc[i] = 0.f;
#pragma unroll 1
  for (int k = 0; k < 31; k++) {
    const int s = k & 3;
    const bool pend = k > 0 && tid < NREL;
    mbar_wait(bars + (B_FULL + s) * 8, (k >> 2) & 1);
    if (tid == 0 && wg == 0 && (k & 3) == 0) PSTAMP(44 + (k >> 2));
    if (tid == 0 && wg == 0) PK(6, k);
    if (tid == 0 && wg == 0) PG(k);
    const uint32_t st = sb + s * STG_BYTES;
    const uint64_t da = make_desc(st + wg * 8192, 16, 1024, 1), db = make_desc(st + A_BYTES, 2048, 512, 2);
#pragma unroll
    for (int kk = 0; kk < 4; kk++) {
      wg_fence();
      ss160<1, 0>(acc, da + kk * 2, db + (kk >> 1) * (B_BYTES / 32) + (kk & 1) * 64, 1);
      wg_commit();
      wg_wait<1>();
      if (kk == 0 && pend) mbar_arrive_rem(rel + ((k + 3) & 3) * 8);
    }
  }
  if (tid == 0 && wg == 0) { uint32_t smid; asm("mov.u32 %0, %%smid;" : "=r"(smid)); PRAW(36, smid); }
  const int row = 16 * w + (lane & 7) + 8 * ((lane >> 3) & 1);
  const uint32_t sa0 = sb + wg * 4096 + row * 64 + (((lane >> 4) ^ ((row >> 1) & 3)) << 4), sa1 = sa0 ^ 32;
  uint32_t pk[40];
  {
    const uint64_t da = make_desc(sb + 3 * STG_BYTES + wg * 8192, 16, 1024, 1), db = make_desc(sb + 3 * STG_BYTES + A_BYTES, 2048, 512, 2);
    mbar_wait(bars + (B_FULL + 3) * 8, 1);
    if (tid == 64) PQ(1 + 2 * wg, 27);
    wg_wait<0>();
    if (tid == 64) PQ(1 + 2 * wg, 28);
#pragma unroll
    for (int i = 0; i < 80; i++) asm volatile("mov.b32 %0, %1;" : "=f"(acc[i]) : "f"(acc[i]) : "memory");
    wg_fence();
#pragma unroll
    for (int kk = 0; kk < 4; kk++) ss64<1, 0>(acc, da + kk * 2, db + (kk >> 1) * (B_BYTES / 32) + (kk & 1) * 64, 1);
    wg_commit();
#pragma unroll
    for (int kk = 0; kk < 4; kk++) ss96<1, 32>(acc, da + kk * 2, db + 256 + (kk >> 1) * (B_BYTES / 32) + (kk & 1) * 64, 1);
    wg_commit();
    mbar_wait(bars + B_EMPTY * 8, 1);
    if (tid == 64) PQ(1 + 2 * wg, 29);
    wg_wait<1>();
    if (tid == 64) PQ(1 + 2 * wg, 30);
#pragma unroll
    for (int i = 0; i < 32; i++) asm volatile("" : "+f"(acc[i])::"memory");
#pragma unroll
    for (int i = 0; i < 16; i++) { pk[i] = pack_bf16(acc[2 * i], acc[2 * i + 1]); asm volatile("" : "+r"(pk[i])::"memory"); }
    stsm4(sa0 + j * 8192, pk[0], pk[1], pk[2], pk[3]);
    stsm4(sa1 + j * 8192, pk[4], pk[5], pk[6], pk[7]);
    stsm4(sa0 + OFF_SP1 + 4096 - wg * 8192, pk[8], pk[9], pk[10], pk[11]);
    stsm4(sa1 + OFF_SP1 + 4096 - wg * 8192, pk[12], pk[13], pk[14], pk[15]);
    fence_async();
    __syncwarp();
    if (lane == 0) mbar_arrive(bv + B_STAGED * 8);
    if (tid == 64) PQ(1 + 2 * wg, 31);
    mbar_wait(bars + B_WFULL * 8, 0);
    mbar_wait(bars + (B_WFULL + 2) * 8, 0);
    mbar_wait(bars + (B_WFULL + 3) * 8, 0);
  }
  wg_wait<0>();
#pragma unroll
  for (int i = 32; i < 80; i++) asm volatile("" : "+f"(acc[i])::"memory");
  if (tid == 0 && wg == 0) { PSTAMP(2); PG(30); }
    if (tid == 64) PQ(1 + 2 * wg, 21);
  if (tid < 3) mbar_arrive_rem(mapa(bars + B_PFREE * 8, CL == 8 ? half * 4 + ((j + 1 + tid) & 3) : rank));
  if (tid == 32) mbar_arrive(bv + B_DRAIN * 8);
#pragma unroll
  for (int i = 16; i < 40; i++) { pk[i] = pack_bf16(acc[2 * i], acc[2 * i + 1]); asm volatile("" : "+r"(pk[i])::"memory"); }
  const uint64_t dw0 = make_desc(sb + OFF_D, 16, 512, 2);
  mbar_wait(bars + (B_WFULL + 1) * 8, 0);
  wg_fence();
  RS<160>::first(acc, &pk[0], dw0);
  RS<160>::run(acc, &pk[4], dw0 + 2, 1);
  RS<160>::run(acc, &pk[8], dw0 + (W_BYTES / 16), 1);
  RS<160>::run(acc, &pk[12], dw0 + (W_BYTES / 16) + 2, 1);
  wg_commit();
    if (tid == 64) PQ(1 + 2 * wg, 22);
  mbar_wait(bars + B_DRAIN * 8, 0);
    if (tid == 64) PQ(1 + 2 * wg, 23);
  stsm4(sa0 + OFF_R0 + j * 8192, pk[16], pk[17], pk[18], pk[19]);
  stsm4(sa1 + OFF_R0 + j * 8192, pk[20], pk[21], pk[22], pk[23]);
  stsm4(sa0 + OFF_SP4, pk[24], pk[25], pk[26], pk[27]);
  stsm4(sa1 + OFF_SP4, pk[28], pk[29], pk[30], pk[31]);
  stsm4(sa0 + OFF_R1 + j * 8192, pk[32], pk[33], pk[34], pk[35]);
  stsm4(sa1 + OFF_R1 + j * 8192, pk[36], pk[37], pk[38], pk[39]);
    if (tid == 64) PQ(1 + 2 * wg, 24);
  fence_async();
  __syncwarp();
  if (lane == 0) mbar_arrive(bv + (B_STAGED + 1) * 8);
    if (tid == 64) PQ(1 + 2 * wg, 25);
  wg_fence();
#pragma unroll
  for (int n = 2; n < 4; n++) {
    RS<160>::run(acc, &pk[8 * n], dw0 + n * (W_BYTES / 16), 1);
    RS<160>::run(acc, &pk[8 * n + 4], dw0 + n * (W_BYTES / 16) + 2, 1);
    wg_commit();
  }
  uint64_t dp[3];
  uint32_t pb[3], rl[3];
#pragma unroll
  for (int ps = 0; ps < 3; ps++) {
    const int src = ps + (ps >= j);
    dp[ps] = make_desc(sb + src * 8192 + wg * 4096, 16, 512, 2);
    pb[ps] = bars + (B_PFULL + src) * 8;
    rl[ps] = mapa(bars + (B_PFREE + 1) * 8, CL == 8 ? half * 4 + src : rank);
  }
  wg_wait<2>();
  if (tid == 32 || tid == 33) mbar_arrive(bv + (B_WEMPTY + tid - 32) * 8);
  mbar_wait(pb[0], 0);
  wg_wait<1>();
  if (tid == 32) mbar_arrive(bv + (B_WEMPTY + 2) * 8);
    if (tid == 64) PQ(1 + 2 * wg, 26);
#pragma unroll
  for (int n = 4; n < 17; n++) {
    const int m = n - 4 - (n > 10), r = m / 3, ps = m % 3;
    const uint64_t dw = dw0 + (int)(w_off(n % NW) - OFF_D) / 16;
    wg_fence();
    if (n == 10) {
      RS<160>::run(acc, &pk[32], dw, 1);
      RS<160>::run(acc, &pk[36], dw + 2, 1);
    } else {
      const uint64_t d = dp[ps] + pslot_off(r, 0) / 16 + (r == 1 ? 256 - wg * 512 : 0);
      ss160<0, 0>(acc, d, dw, 1);
      ss160<0, 0>(acc, d + 2, dw + 2, 1);
    }
    wg_commit();
    if (tid == 64) PQ(1 + 2 * wg, n + 1);
    if (n == 9) mbar_wait(bars + (B_WFULL + 4) * 8, 0);
    else {
      const int m1 = n - 3 - (n > 9);
      mbar_wait(pb[m1 % 3] + (m1 / 3) * 32, 0);
      if (tid == 0 && wg == 0 && m1 < 6 && m1 % 3 != 1) PSTAMP(22 + (m1 / 3) * 2 + ((m1 % 3) >> 1));
      if (tid == 0 && wg == 0 && m1 % 6 == 0) PSTAMP(3 + m1 / 6);
    }
    if (tid == 64) PQ(2 + 2 * wg, n + 1);
    wg_wait<1>();
    if (n <= 20 - NW && tid == 32) mbar_arrive(bv + (B_WEMPTY + n - 1) * 8);
    const int mp = n - 5 - (n > 11);
    if (n > 4 && n != 11 && mp < 6 && tid == 0) mbar_arrive_rem(rl[mp % 3] + (mp / 3) * 8);
    if (n == 14 && tid == 0) mbar_arrive(bv + B_R1FREE * 8);
  }
  auto tail = [&](auto H) {
    constexpr int SO = H.value ? 0 : 40, KO = 40 - SO;
    wg_wait<0>();
#pragma unroll
    for (int i = 0; i < 80; i++) asm volatile("mov.b32 %0, %1;" : "=f"(acc[i]) : "f"(acc[i]) : "memory");
#pragma unroll
    for (int n = 17; n < 20; n++) {
      const int m = n - 5, m1 = n - 4;
      const uint64_t dw = dw0 + (int)(w_off(n % NW) - OFF_D) / 16 + SO * 8, d = dp[m % 3] + pslot_off(m / 3, 0) / 16;
      wg_fence();
      ss80<0, SO>(acc, d, dw, 1);
      ss80<0, SO>(acc, d + 2, dw + 2, 1);
      wg_commit();
      if (tid == 64) PQ(1 + 2 * wg, n + 1);
      if (n < 19) mbar_wait(pb[m1 % 3] + (m1 / 3) * 32, 0);
      if (tid == 64) PQ(2 + 2 * wg, n + 1);
    }
    auto keep = [&](int n0, int n1) {
      wg_fence();
#pragma unroll
      for (int n = n0; n < n1; n++) {
        const int m = n - 5;
        const uint64_t dw = dw0 + (int)(w_off(n % NW) - OFF_D) / 16 + KO * 8, d = dp[m % 3] + pslot_off(m / 3, 0) / 16;
        ss80<0, KO>(acc, d, dw, 1);
        ss80<0, KO>(acc, d + 2, dw + 2, 1);
      }
      wg_commit();
    };
    keep(17, 18);
    uint32_t tx;
    asm volatile("mov.u32 %0, %%tid.x;" : "=r"(tx));
    const int wg = tx >> 7, w = (tx >> 5) & 3, lane = tx & 31;
    const uint32_t xw = sb + OFF_R1 + wg * 10240 + w * 2560;
    const uint32_t xl = xw + lane * 16;
    const uint32_t xr = mapa(xl, rank ^ (CL / 2));
    const uint32_t xb = mapa(bars + (B_XFULL + (tx >> 5)) * 8, rank ^ (CL / 2));
    mbar_wait(bars + B_XFREE * 8, 0);
    wg_wait<1>();
#pragma unroll
    for (int i = 0; i < 40; i++) asm volatile("" : "+f"(acc[SO + i])::"memory");
    if (tx == 0) PSTAMP(37);
#pragma unroll
    for (int i = 0; i < 5; i++)
      st_async4(xr + i * 512, pack_bf16(acc[SO + 8 * i], acc[SO + 8 * i + 1]), pack_bf16(acc[SO + 8 * i + 2], acc[SO + 8 * i + 3]),
                pack_bf16(acc[SO + 8 * i + 4], acc[SO + 8 * i + 5]), pack_bf16(acc[SO + 8 * i + 6], acc[SO + 8 * i + 7]), xb);
    if (tx == 0) PSTAMP(38);
    keep(18, 20);
    wg_wait<0>();
#pragma unroll
    for (int i = 0; i < 40; i++) asm volatile("" : "+f"(acc[KO + i])::"memory");
    if (tx == 0) PSTAMP(6);
#pragma unroll
    for (int i = 0; i < 20; i++) { pk[i] = pack_bf16(acc[KO + 2 * i], acc[KO + 2 * i + 1]); asm volatile("" : "+r"(pk[i])::"memory"); }
    const uint32_t oa = xw + (lane & 15) * 160 + (lane >> 4) * 16;
    mbar_wait(bars + (B_XFULL + (tx >> 5)) * 8, 0);
    if (tx == 0) PSTAMP(39);
#pragma unroll
    for (int i = 0; i < 5; i++) {
      const uint4 rv = lds128(xl + i * 512);
#pragma unroll
      for (int c = 0; c < 4; c++) {
        const uint32_t o = ((const uint32_t*)&rv)[c];
        pk[4 * i + c] = H.value ? bfma(pk[4 * i + c], 0xbf80bf80u, o) : bfma(o, 0xbf80bf80u, pk[4 * i + c]);
      }
    }
#pragma unroll
    for (int i = 0; i < 20; i++) asm volatile("" : "+r"(pk[i])::"memory");
    __syncwarp();
#pragma unroll
    for (int i = 0; i < 5; i++) stsm4(oa + i * 32, pk[4 * i], pk[4 * i + 1], pk[4 * i + 2], pk[4 * i + 3]);
    fence_async();
    __syncwarp();
    if (lane == 0) {
      if (tx == 0) PSTAMP(40);
      tma_store2d(mOa, xw, j * 160 + H.value * 80, tt * 128 + wg * 64 + w * 16);
      bulk_commit();
      bulk_wait_read();
    }
  };
  if (half) tail(IC<1>{});
  else tail(IC<0>{});
  if (tid == 0 && wg == 0) { PSTAMP(7); PGT(63); PG(31); PQD(6); PQD(7); }
  if (tid == 64) { PQD(1 + 2 * wg); PQD(2 + 2 * wg); }
}

template <int CL>
__global__ void __launch_bounds__(512, 1) __cluster_dims__(CL, 1, 1)
fused_kernel(const __grid_constant__ Params p, const __grid_constant__ CUtensorMap mCr, const __grid_constant__ CUtensorMap mCi,
             const __grid_constant__ CUtensorMap mX, const __grid_constant__ CUtensorMap mWr, const __grid_constant__ CUtensorMap mWi,
             const __grid_constant__ CUtensorMap mKin, const __grid_constant__ CUtensorMap mVin, const __grid_constant__ CUtensorMap mQ,
             const __grid_constant__ CUtensorMap mOa, const __grid_constant__ CUtensorMap mOb) {
  extern __shared__ __align__(1024) unsigned char smem[];
  const uint32_t sb = smem_u32(smem);
  const uint32_t bars = sb + OFF_BAR;
  const int wg = __shfl_sync(0xffffffffu, threadIdx.x >> 7, 0);
  const int tid = threadIdx.x & 127, lane = threadIdx.x & 31;
  const int warp = __shfl_sync(0xffffffffu, tid >> 5, 0);
  const uint32_t ctouch = ((const uint32_t*)&p)[tid < 32 ? -52 : tid < 64 ? -30 : tid < 96 ? 0 : 12];
  uint32_t rank;
  asm("mov.u32 %0, %%cluster_ctarank;" : "=r"(rank));
  const int cid = blockIdx.x / CL;
  constexpr int SEGS = 8 / CL;
  bool gemm;
  int tt, half, j, oct0, noct;
  if (CL == 8) {
    gemm = true; tt = cid; half = rank >> 2; j = rank & 3; oct0 = cid; noct = 5;
  } else {
    const int ti = cid / 6, c6 = cid % 6;
    tt = p.nA + ti; half = rank; j = c6 & 3; gemm = c6 < 4;
    oct0 = tt + (c6 == 5 ? 48 : 0);
    noct = gemm ? 0 : (c6 == 4 ? 3 : 2);
  }
  const uint32_t ubase = CL == 8 ? sb + OFF_U : sb;
  if (threadIdx.x == 0) { PSTAMP(0); PGT(62); }
  if (threadIdx.x > 64 && threadIdx.x < 126 && threadIdx.x != 64 + 52 && threadIdx.x != 64 + 54) PZERO(threadIdx.x - 64, threadIdx.x - 64);
  const int gw = (wg * 4 + warp + (gemm ? 4 : 1)) & 15;
  const CUtensorMap* mC = half ? &mCi : &mCr;
  if (gemm && gw == 4) pf256(sb + OFF_DUMMY + lane * 4, (half ? p.ci : p.cr) + (size_t)(tt * 128 + j * 32 + lane) * 2048);
  {
    const uint64_t cntt = CL == 8 ? 0x22111411111862A1ull : (gemm ? 0x2211111111186241ull : 0x1114441111111C11ull);
    const uint32_t cnt = (uint32_t)(cntt >> (4 * gw)) & 15;
    if (elect_one()) {
#pragma unroll
      for (int i = 0; i < 8; i++) mbar_init(bars + gw * 64 + i * 8, cnt);
      asm volatile("fence.mbarrier_init.release.cluster;" ::: "memory");
    }
    __syncwarp();
  }
  if (threadIdx.x == 384) PSTAMP(52);
  cluster_arrive();
  if (gemm && (gw == 1 || gw == 2) && elect_one()) pf_map(gw == 1 ? mC : &mX);
  if (threadIdx.x == 384) PSTAMP(54);
  auto load_stage = [&](int k, int s) {
    const uint32_t fb = bars + (B_FULL + s) * 8, st = sb + s * STG_BYTES;
    mbar_expect_tx(fb, STG_BYTES);
    if (CL == 8) {
      tma2d_mc(st + j * 4096, mC, k * 64, tt * 128 + j * 32, fb, (uint16_t)(0xF << (4 * half)));
      tma3d_mc(st + A_BYTES + half * (B_BYTES / 2), &mX, 0, k * 64 + 32 * half, j * 5, fb, (uint16_t)(0x11 << j));
    } else {
      tma3d_mc(st + A_BYTES + half * (B_BYTES / 2), &mX, 0, k * 64 + 32 * half, j * 5, fb, (uint16_t)3);
#pragma unroll
      for (int i = 0; i < 4; i++) tma2d(st + i * 4096, mC, k * 64, tt * 128 + i * 32, fb);
    }
  };
  if (gemm && gw == 0) {
    if (lane == 0) PSTAMP(55);
    cluster_wait();
    if (lane == 0) PSTAMP(56);
    if (elect_one()) {
#pragma unroll 1
      for (int s = 0; s < 4; s++) load_stage(s, s);
      PSTAMP(57);
    }
    __syncwarp();
  }
  if (CL == 8) asm volatile("griddepcontrol.launch_dependents;");
  if (lane < 8) {
    const int i = gw * 8 + lane;
    uint32_t tx = 0;
    if ((i >= B_UFULL && (!gemm || i < B_WEMPTY)) || (i >= B_OFULL8 && i < B_KBAR)) tx = 4096;
    if (gemm && i >= B_PFULL && i < B_QFULL8) tx = 8192 + W_BYTES;
    if (gw == B_WFULL / 8) tx = W_BYTES;
    if (gemm && gw == B_XFULL / 8) tx = 2560;
    if (CL == 8 ? (i >= B_LFULL8 && i < B_LFULL8 + 5) : (!gemm && i < 12)) tx = LSET_TX;
    if (tx) mbar_expect_tx(bars + i * 8, tx);
  }
  if (wg == 1 && warp < 2 && noct > 0 && elect_one()) pf_map(warp ? &mVin : &mKin);
  __syncwarp();
  const uint32_t dummy = sb + OFF_DUMMY + lane * 4;
  const int pt = CL == 8 ? warp : wg * 4 + warp;

  Maps mp;
  mp.k = &mKin; mp.v = &mVin; mp.q = &mQ; mp.ob = &mOb;
  if (wg < 3) {
    if (gemm && wg < 2) {
      asm volatile("{\n.reg .pred p;\nsetp.eq.u32 p, %0, 0x9e3779b9;\n@p st.shared.u32 [%1], %0;\n}\n" ::"r"(ctouch), "r"(dummy) : "memory");
      if (threadIdx.x == 0) PSTAMP(11);
      cluster_wait();
      if (threadIdx.x == 0) PSTAMP(1);
      gemm_consumer<CL>(&mOa, sb, wg, tid, rank, half, j, tt);
      if (threadIdx.x == 0) { PDUMP(0, 7); PDUMP(34, 40); PDUMP(11, 11); PDUMP(22, 25); PDUMP(44, 51); PDUMP(62, 63); }
    } else if (noct > 0) {
      const uint32_t kbase = CL == 8 ? sb + OFF_K : sb + OFF_K2 + wg * KBUF;
      const int first = CL == 8 ? 0 : wg, nch = noct * SEGS, barid = CL == 8 ? 1 : 1 + wg;
      uint2 pw = p0_w(p, oct0 + (CL == 8 ? 0 : 16 * (pt >> 3)), lane);
      for (int i = first + (CL == 8 ? warp : 3 * warp); i < nch; i += (CL == 8 ? 4 : 12)) sts128(ubase + i * USLOT + 4096 + lane * 16, 0, 0, 0, 0);
      fence_async();
      if (CL == 8 && tid == 0) PSTAMP(28);
      cluster_wait();
      if (CL == 8 && tid == 0) PSTAMP(29);
      if (CL == 8) {
        p0_task<CL, 2>(pw, sb, ubase, sb + OFF_OST, bars + B_LFULL8 * 8, 0, rank * 256, 2 * warp, lane);
      } else {
#pragma unroll 1
        for (int t = pt; t < noct * 8; t += 12) {
          if (t >= 12) pw = p0_w(p, oct0 + 16 * (t >> 3), lane);
          p0_task<CL, 4>(pw, sb, ubase, sb + OFF_L2 + (t >> 1) * LSET, bars + (B_LFULL2 + (t >> 1)) * 8, t >> 3, rank * 1024 + ((t >> 1) & 3) * 256, (t & 1) * 4, lane);
        }
        __syncwarp();
        if (lane == 0) mbar_arrive(bars + B_DRAIN * 8);
      }
      bar_sync(barid, 128);
      if (threadIdx.x == 256) PSTAMP(8);
      if (CL == 2) asm volatile("setmaxnreg.inc.sync.aligned.u32 136;");
      conv_main<CL>(sb, ubase, kbase, bars + (B_KBAR + (CL == 8 ? 0 : wg * 8)) * 8, rank, first, nch, tid);
      if (CL == 2 && wg == 2) {
        const int t = nch - 4 + warp;
        conv_out<CL>(mp, sb, sb + OFF_Q2 + t * 4096, bars + (B_QFULL2 + t) * 8, 0, oct0 + 16 * (noct - 1), t, rank * 4 + warp, -1, lane);
      }
      if (threadIdx.x == 256) { PSTAMP(9); PDUMP(8, 9); PDUMP(12, (CL == 8 ? 21 : 43)); PDUMP(28, 29); PDUMP(41, 43); }
      if (CL == 2 && threadIdx.x == 0) { PDUMP(0, 0); PDUMP(62, 62); }
    } else {
      cluster_wait();
      if (CL == 2 && gemm && warp < 3 && lane == 0) {
        const int src = (j + 1 + warp) & 3;
        const unsigned char* scr = p.pscr + (size_t)(tt * 8 + half * 4 + src) * 40960;
        unsigned int* fl = p.flag + (tt * 8 + half * 4 + src) * 4 + warp;
#pragma unroll 1
        for (int r = 0; r < 5; r++) {
          if (r != 2) mbar_wait(bars + (r == 0 ? B_STAGED : r == 1 ? B_PFREE : B_PFREE + r - 2) * 8, 0);
          unsigned int f, it = 0;
          while (true) {
            asm volatile("ld.relaxed.gpu.global.u32 %0, [%1];" : "=r"(f) : "l"(fl) : "memory");
            if (f > (unsigned)r) break;
            if (++it > (1u << 22)) __trap();
          }
          asm volatile("fence.proxy.async.global;" ::: "memory");
          bulk_g2s(sb + pslot_off(r, src), scr + r * 8192, 8192, bars + (B_PFULL + r * 4 + src) * 8);
        }
        asm volatile("st.relaxed.gpu.global.u32 [%0], %1;" ::"l"(fl), "r"(0u) : "memory");
      }
    }
  } else {
    KRegs kr;
    if (noct > 0 && (CL == 8 ? warp == 2 : warp < 3)) k_load(p, kr, oct0 * 8 + rank * (8 / CL) + (CL == 8 ? 0 : warp), lane);
    if (CL == 2 && warp == 3 && lane == 0 && noct > 0) {
#pragma unroll 1
      for (int b = 0; b < 32; b++)
        p0_issue(mp, sb + OFF_L2 + (b >> 2) * LSET, bars + (B_LFULL2 + (b >> 2)) * 8, oct0 + 16 * (b >> 4), rank * 1024 + ((b >> 2) & 3) * 256, b & 3);
    }
    if (threadIdx.x == 384) PSTAMP(53);
    __syncwarp();
    if (CL == 2 && !gemm) {
      asm volatile("setmaxnreg.dec.sync.aligned.u32 96;");
      if (warp < 3 && noct > 0) k_builder<CL>(p, kr, sb + OFF_K2 + warp * KBUF, bars + (B_KBAR + warp * 8) * 8, rank, oct0, warp, noct * SEGS, lane);
      else {
        cluster_wait();
        if (noct > 0) {
          if (lane == 0) {
#pragma unroll 1
            for (int b = 32; b < noct * 16; b++)
              p0_issue(mp, sb + OFF_L2 + (b >> 2) * LSET, bars + (B_LFULL2 + (b >> 2)) * 8, oct0 + 16 * (b >> 4), rank * 1024 + ((b >> 2) & 3) * 256, b & 3);
          }
          mbar_wait(bars + B_DRAIN * 8, 0);
          if (lane == 0) {
#pragma unroll 1
            for (int t = 0; t < noct * 4; t++) {
              mbar_expect_tx(bars + (B_QFULL2 + t) * 8, 4096);
              tma3d(sb + OFF_Q2 + t * 4096, mp.q, (oct0 + 16 * (t >> 2)) * 8, (rank * 4 + (t & 3)) * 16, 0, bars + (B_QFULL2 + t) * 8);
            }
          }
          __syncwarp();
#pragma unroll 1
          for (int t = 0; t < noct * 4 - 4; t++)
            conv_out<CL>(mp, sb, sb + OFF_Q2 + t * 4096, bars + (B_QFULL2 + t) * 8, 0, oct0 + 16 * (t >> 2), t, rank * 4 + (t & 3), -1, lane);
        }
      }
      return;
    }
    asm volatile("setmaxnreg.dec.sync.aligned.u32 %0;" ::"n"(RG_H));
    if ((warp & 3) == 0) {
      const CUtensorMap* mW = half ? &mWi : &mWr;
      if (elect_one()) {
        if (CL == 8) {
#pragma unroll 1
          for (int b = 0; b < 4; b++) p0_issue(mp, sb + OFF_OST, bars + B_LFULL8 * 8, oct0, rank * 256, b);
          PSTAMP(43);
        }
#pragma unroll 1
        for (int lap = 1; lap < 8; lap++) {
#pragma unroll
          for (int s = 0; s < 4; s++) {
            mbar_wait(bars + (B_EMPTY + s) * 8, (lap + 1) & 1);
            PK(7, lap * 4 + s);
            load_stage(lap * 4 + s, s);
            if (s == 3 && lap == 5) { pf_map(mW); pf_map(&mOa); }
            if (CL == 8 && lap < 5) p0_issue(mp, sb + OFF_D + (lap - 1) * LSET, bars + (B_LFULL8 + lap) * 8, oct0 + 16 * lap, rank * 256, s);
            if (CL == 2 && lap == 6 && s < 3) tma2d(sb + OFF_D + s * W_BYTES, mW, j * 160 + s * 32, j * 160, bars + (B_WFULL + s) * 8);
          }
        }
#pragma unroll
        for (int n = 3; n < 20; n++) {
          if (CL == 8 && n == 3) { mbar_wait(bars + B_UFREE * 8, 0); mbar_wait(bars + B_P0DONE * 8, 0); }
          if (n == 5) mbar_wait(bars + (B_EMPTY + 1) * 8, 1);
          if (n == 8) mbar_wait(bars + B_C1DONE * 8, 0);
          const int ws = n % NW;
          if (n >= NW) mbar_wait(bars + (B_WEMPTY + n - NW) * 8, 0);
          const int m = n - 4 - (n > 10), r = m / 3, ps = m - 3 * r, src = ps + (ps >= j);
          const int col = n == 3 ? j * 160 + 96 : n == 10 ? j * 160 + 128 : src * 160 + r * 32;
          PQ(0, n);
          tma2d(sb + w_off(ws), mW, col, j * 160, bars + (n == 3 ? B_WFULL + 3 : n == 10 ? B_WFULL + 4 : B_PFULL + r * 4 + src) * 8);
        }
        PDUMP(52, 58); PQD(0);
      }
    } else if (warp > 2) {
      cluster_wait();
      if (CL == 8) {
#pragma unroll 1
        for (int t = 1; t < 5; t++) {
          p0_task<CL, 8>(p0_w(p, oct0 + 16 * t, lane), sb, ubase, sb + OFF_D + (t - 1) * LSET, bars + (B_LFULL8 + t) * 8, t, rank * 256, 0, lane);
          if (lane == 0) PSTAMP(29 + t);
        }
        __syncwarp();
        if (lane == 0) {
#pragma unroll 1
          for (int s = 0; s < 3; s++) tma2d(sb + OFF_D + s * W_BYTES, half ? &mWi : &mWr, j * 160 + s * 32, j * 160, bars + (B_WFULL + s) * 8);
          mbar_arrive(bars + B_P0DONE * 8);
          PDUMP(30, 33);
        }
      }
      if (lane == 0) {
        unsigned char* scr = p.pscr + (size_t)(tt * 8 + half * 4 + j) * 40960;
        unsigned int* fl = p.flag + (tt * 8 + half * 4 + j) * 4;
        const uint16_t mask = (uint16_t)((0xF ^ (1 << j)) << (4 * half));
        auto put = [&](int r) { bulk_s2g(scr + r * 8192, sb + stg_off(r, j), 8192); bulk_commit(); };
        mbar_wait(bars + B_STAGED * 8, 0);
        PSTAMP(26);
        put(0);
        put(1);
#pragma unroll
        for (int r = 0; r < 5; r++) {
          if (r == 2) mbar_wait(bars + (B_STAGED + 1) * 8, 0);
          if (r == 0) { bulk_wait<1>(); PSTAMP(59); }
          if (r == 1) { bulk_wait<0>(); mbar_arrive(bars + B_C1DONE * 8); }
          if (CL == 2) {
            if (r == 2) { put(2); put(3); put(4); bulk_wait<2>(); }
            if (r == 3) bulk_wait<1>();
            if (r == 4) bulk_wait<0>();
          } else if (r >= 2) { put(r); bulk_wait<0>(); }
          if (r == 2) PSTAMP(60);
          if (r == 4) PSTAMP(61);
          if (CL == 8) {
            if (r == 1 || r > 2) mbar_wait(bars + (r == 1 ? B_PFREE : B_PFREE + r - 2) * 8, 0);
            if (r == 1) PSTAMP(27);
            PQ(5, r);
            bulk_g2s_mc(sb + pslot_off(r, j), scr + r * 8192, 8192, bars + (B_PFULL + r * 4 + j) * 8, mask);
          } else {
            asm volatile("fence.proxy.async.global;" ::: "memory");
#pragma unroll
            for (int i = 0; i < 3; i++) asm volatile("st.relaxed.gpu.global.u32 [%0], %1;" ::"l"(fl + i), "r"(r + 1) : "memory");
          }
        }
        mbar_wait(bars + B_R1FREE * 8, 0);
        mbar_arrive_rem(mapa(bars + B_XFREE * 8, rank ^ (CL / 2)));
        PDUMP(59, 61); PDUMP(26, 27); PQD(5);
      }
    } else if (warp & 2) {
      if (CL == 8) k_builder<CL>(p, kr, sb + OFF_K, bars + B_KBAR * 8, rank, oct0, 0, noct, lane);
      else cluster_wait();
    } else {
      cluster_wait();
      if (CL == 8) {
        const uint32_t qb = sb + OFF_OST + 8192, qbar = bars + B_QFULL8 * 8;
        mbar_wait(bars + B_UFULL * 8, 0);
        if (lane == 0) { mbar_expect_tx(qbar, 4096); tma3d(qb, mp.q, oct0 * 8, rank * 16, 0, qbar); }
#pragma unroll 1
        for (int t = 0; t < 5; t++) conv_out<CL>(mp, sb, qb, qbar, t & 1, oct0 + 16 * t, t, rank, t < 4 ? oct0 + 16 * t + 16 : -1, lane);
        if (lane == 0) { PSTAMP(10); PDUMP(10, 10); }
      }
    }
  }
}

typedef CUresult (*PFN_encodeTiled)(CUtensorMap*, CUtensorMapDataType, cuuint32_t, void*, const cuuint64_t*, const cuuint64_t*, const cuuint32_t*,
                                    const cuuint32_t*, CUtensorMapInterleave, CUtensorMapSwizzle, CUtensorMapL2promotion, CUtensorMapFloatOOBfill);

void make_map(PFN_encodeTiled enc, CUtensorMap* m, const void* ptr, int rank, const cuuint64_t* dims, const cuuint64_t* strides, const cuuint32_t* box,
              CUtensorMapSwizzle swz, CUtensorMapL2promotion prom) {
  cuuint32_t es[5] = {1, 1, 1, 1, 1};
  enc(m, CU_TENSOR_MAP_DATA_TYPE_BFLOAT16, rank, const_cast<void*>(ptr), dims, strides, box, es, CU_TENSOR_MAP_INTERLEAVE_NONE, swz, prom,
      CU_TENSOR_MAP_FLOAT_OOB_FILL_NONE);
}

}

extern "C" void kernel_launch(void* const* d_in, const int* in_sizes, int n_in, void* d_out, int out_size) {
  static PFN_encodeTiled enc = nullptr;
  static int nA = -1;
  static void *pscr = nullptr, *flag = nullptr, *prof = nullptr;
  cudaStream_t st = cudaStreamPerThread;
  cudaLaunchConfig_t cfg = {};
  cudaLaunchAttribute at[2];
  cfg.blockDim = dim3(512);
  cfg.dynamicSmemBytes = SMEM_BYTES;
  cfg.stream = st;
  cfg.attrs = at;
  at[0].id = cudaLaunchAttributeClusterDimension;
  at[0].val.clusterDim.y = 1;
  at[0].val.clusterDim.z = 1;
  if (nA < 0) {
    void* fn = nullptr;
    cudaDriverEntryPointQueryResult qr;
    cudaGetDriverEntryPoint("cuTensorMapEncodeTiled", &fn, cudaEnableDefault, &qr);
    enc = (PFN_encodeTiled)fn;
    cudaFuncSetAttribute(fused_kernel<8>, cudaFuncAttributeMaxDynamicSharedMemorySize, SMEM_BYTES);
    cudaFuncSetAttribute(fused_kernel<2>, cudaFuncAttributeMaxDynamicSharedMemorySize, SMEM_BYTES);
    cudaGetSymbolAddress(&pscr, g_pscr);
    cudaGetSymbolAddress(&flag, g_flag);
    int nc = 0;
    cfg.gridDim = dim3(128);
    at[0].val.clusterDim.x = 8;
    cfg.numAttrs = 1;
    if (cudaOccupancyMaxActiveClusters(&nc, fused_kernel<8>, &cfg) != cudaSuccess) nc = 0;
    nA = nc > 16 ? 16 : nc;
  }
  CUtensorMap mCr, mCi, mX, mWr, mWi, mKin, mVin, mQ, mOa, mOb;
  {
    cuuint64_t d[2] = {2048, 2048}, s[1] = {4096};
    cuuint32_t b[2] = {64, 32};
    make_map(enc, &mCr, d_in[1], 2, d, s, b, CU_TENSOR_MAP_SWIZZLE_128B, CU_TENSOR_MAP_L2_PROMOTION_L2_128B);
    make_map(enc, &mCi, d_in[2], 2, d, s, b, CU_TENSOR_MAP_SWIZZLE_128B, CU_TENSOR_MAP_L2_PROMOTION_L2_128B);
  }
  {
    cuuint64_t d[3] = {32, 2048, 20}, s[2] = {1280, 64};
    cuuint32_t b[3] = {32, 32, 5};
    make_map(enc, &mX, d_in[0], 3, d, s, b, CU_TENSOR_MAP_SWIZZLE_64B, CU_TENSOR_MAP_L2_PROMOTION_L2_128B);
  }
  {
    cuuint64_t d[2] = {640, 640}, s[1] = {1280};
    cuuint32_t b[2] = {32, 160};
    make_map(enc, &mWr, d_in[3], 2, d, s, b, CU_TENSOR_MAP_SWIZZLE_64B, CU_TENSOR_MAP_L2_PROMOTION_L2_128B);
    make_map(enc, &mWi, d_in[4], 2, d, s, b, CU_TENSOR_MAP_SWIZZLE_64B, CU_TENSOR_MAP_L2_PROMOTION_L2_128B);
  }
  {
    cuuint64_t d[3] = {640, 512, 4}, s[2] = {5120, 1280};
    cuuint32_t bk[3] = {8, 65, 2};
    make_map(enc, &mKin, d_in[6], 3, d, s, bk, CU_TENSOR_MAP_SWIZZLE_NONE, CU_TENSOR_MAP_L2_PROMOTION_L2_128B);
    make_map(enc, &mVin, d_in[7], 3, d, s, bk, CU_TENSOR_MAP_SWIZZLE_NONE, CU_TENSOR_MAP_L2_PROMOTION_L2_128B);
  }
  {
    cuuint64_t d[3] = {640, 128, 16}, s[2] = {20480, 1280}, d3[3] = {1280, 128, 16}, s3[2] = {40960, 2560}, d2[2] = {1280, 2048}, s2[1] = {2560};
    cuuint32_t b[3] = {8, 16, 16}, ba[2] = {80, 16};
    make_map(enc, &mQ, d_in[5], 3, d, s, b, CU_TENSOR_MAP_SWIZZLE_NONE, CU_TENSOR_MAP_L2_PROMOTION_L2_128B);
    make_map(enc, &mOb, d_out, 3, d3, s3, b, CU_TENSOR_MAP_SWIZZLE_NONE, CU_TENSOR_MAP_L2_PROMOTION_NONE);
    make_map(enc, &mOa, d_out, 2, d2, s2, ba, CU_TENSOR_MAP_SWIZZLE_NONE, CU_TENSOR_MAP_L2_PROMOTION_NONE);
  }
  Params p;
  p.cr = (const bf16*)d_in[1]; p.ci = (const bf16*)d_in[2];
  p.shift_k = (const bf16*)d_in[8]; p.ssm_k = (const bf16*)d_in[9]; p.ssm_D = (const bf16*)d_in[10];
  p.nA = nA; p.pscr = (unsigned char*)pscr; p.flag = (unsigned int*)flag; p.prof = (long long*)prof;
  if (nA > 0) {
    cfg.gridDim = dim3(nA * 8);
    at[0].val.clusterDim.x = 8;
    cfg.numAttrs = 1;
    cudaLaunchKernelEx(&cfg, fused_kernel<8>, p, mCr, mCi, mX, mWr, mWi, mKin, mVin, mQ, mOa, mOb);
  }
  if (nA < 16) {
    cfg.gridDim = dim3((16 - nA) * 12);
    at[0].val.clusterDim.x = 2;
    at[1].id = cudaLaunchAttributeProgrammaticStreamSerialization;
    at[1].val.programmaticStreamSerializationAllowed = 1;
    cfg.numAttrs = nA > 0 ? 2 : 1;
    cudaLaunchKernelEx(&cfg, fused_kernel<2>, p, mCr, mCi, mX, mWr, mWi, mKin, mVin, mQ, mOa, mOb);
  }
}
```
